```python
import torch

def _softmax(x, axis=-1):
    return torch.softmax(x, dim=axis)
def _gelu(x):
    return torch.nn.functional.gelu(x, approximate="tanh")
def _silu(x):
    return torch.nn.functional.silu(x)
def _sigmoid(x):
    return torch.sigmoid(x)
def _layernorm(x, axis=-1, eps=1e-5):
    m = x.mean(dim=axis, keepdim=True)
    v = x.var(dim=axis, keepdim=True, unbiased=False)
    return (x - m) / torch.sqrt(v + eps)
def _scatter_add(tgt, idx, src, axis=0):
    return tgt.clone().index_add_(axis, idx, src)
def _segment_sum(src, seg, n):
    out = torch.zeros((n,) + src.shape[1:], dtype=src.dtype)
    return out.index_add_(0, seg, src)
def _pad(x, pw):
    flat = tuple(v for pair in reversed(pw) for v in pair)
    return torch.nn.functional.pad(x, flat)

kernel_name = 'standalone__deformable_dcnv1__vision'

def setup_inputs():

    _w = (lambda a: (lambda t: t.to(torch.bfloat16) if t.is_floating_point() else t)(torch.as_tensor(a)))
    H = W = 224
    C = 96
    K = 3
    return {
        "x": _w((lambda *s: torch.randn(*s, dtype=torch.bfloat16) * 0.05)(1, H, W, C)),
        "offset": _w((lambda *s: torch.randn(*s, dtype=torch.bfloat16) * 0.05)(1, H, W, 2 * K * K) * 0.5),
        "w": _w((lambda *s: torch.randn(*s, dtype=torch.bfloat16) * 0.05)(K, K, C, C) * (K * K * C) ** -0.5),
    }

def reference(x, offset, w):
    B, H, W, C = x.shape
    K = 3
    hh = (lambda x, dt: x.to(dt))(torch.arange(H), x.dtype).reshape(1, H, 1)
    ww = (lambda x, dt: x.to(dt))(torch.arange(W), x.dtype).reshape(1, 1, W)
    xf = x.reshape(B, H * W, C)
    def _gather(yi, xi):
        lin = (yi * W + xi).reshape(B, H * W)
        idx = (lambda x, n, axis: torch.repeat_interleave(x, n, dim=axis))(lin[..., None], C, axis=-1)
        return (lambda x, i, axis: torch.take_along_dim(x, i, dim=axis))(xf, idx, axis=1).reshape(B, H, W, C)
    taps = []
    for ki in range(K):
        for kj in range(K):
            t = ki * K + kj
            dy = offset[..., 2 * t]
            dx = offset[..., 2 * t + 1]
            py = torch.clip(hh + (ki - 0.5 * (K - 1)) + dy, 0.0, H - 1.0)
            px = torch.clip(ww + (kj - 0.5 * (K - 1)) + dx, 0.0, W - 1.0)
            y0 = torch.floor(py)
            x0 = torch.floor(px)
            y1 = torch.clip(y0 + 1.0, 0.0, H - 1.0)
            x1 = torch.clip(x0 + 1.0, 0.0, W - 1.0)
            wy = (py - y0)[..., None]
            wx = (px - x0)[..., None]
            y0i = (lambda x, dt: x.to(dt))(y0, torch.int64)
            y1i = (lambda x, dt: x.to(dt))(y1, torch.int64)
            x0i = (lambda x, dt: x.to(dt))(x0, torch.int64)
            x1i = (lambda x, dt: x.to(dt))(x1, torch.int64)
            v = (1 - wy) * (1 - wx) * _gather(y0i, x0i) + (1 - wy) * wx * _gather(y0i, x1i) + wy * (1 - wx) * _gather(y1i, x0i) + wy * wx * _gather(y1i, x1i)
            taps.append(v)
    samp = torch.stack(taps, 3)
    return torch.einsum("bhwkc,kco->bhwo", samp, w.reshape(K * K, C, C))
```

```cpp
#include <cuda_runtime.h>
#include <cuda.h>
#include <cuda_bf16.h>
#include <stdint.h>

namespace {

constexpr int IH = 224, IW = 224, IC = 96;
constexpr int GRID = 132, NW = 72, NG = 48;
constexpr int NTHREADS = 512;
constexpr int STAGE = 18432;
constexpr int WTAP = 3072 >> 4, WHALF = (STAGE / 2) >> 4;
constexpr uint32_t SB = 0x400;
constexpr int VROW = 18 * 64, VSLOT = 8 * VROW, PIECE = 34 * 128;
constexpr int SM_R = 14 * VSLOT, SM_WW = SM_R + 39936;
constexpr int GROW = 10 * 64, GSLICE = 20 * GROW, GWIN = 3 * GSLICE, SM_GW = 2 * GWIN;
constexpr int CROW = 12 * 64, CSLICE = 12 * CROW, CWIN = 3 * CSLICE, SM_CX = 9 * STAGE, SM_CT = SM_CX + 2 * CWIN;
constexpr int SM_FIX = 224256, SM_BAR = 231168, SMEM_BYTES = 232448;
constexpr int HALF = 17 * VROW;
constexpr int B_WF = 0, B_WE = 18, B_XF = 33, B_VF = 53, B_VE = 57, B_RE = 58, B_ST = 59, B_SC = 67, B_UI = 52, B_IM = 51, B_GF = 68, B_GX = 77;
constexpr int O_TGT = 768, O_CNT = 776, O_REC = 784, O_TS = 1024;
constexpr int NREC = 16;
#define FP32T 0
#define BDELAY 1500
#define SDELAY 3000
#define FETCHN 4
#define BLENDN 3
#define PDELAY 2300
#define HOLD 0
#define SDELAY2 800
#define SWAIT 1
#define ODELAY 600
#define NPOLL 4
#define PSTEP 250
#define PF1 0
#define PF2 0
#define PFS 700
#define PIN 1
#define FDELAY 8500
#define CW0 1500
#define CWS 500
#define CX0 1000
#define CXS 2500
#define GX0 2000
#define GX1 2500
#define GXS 2500
#define GW0 2300
#define GWS 900
constexpr float PA = FP32T ? 2.0f / 3.0f : 0.5f, PB = FP32T ? 1.5f : 2.0f;
constexpr float AL = 1.0f - PA * PA / (PB * PB);

struct Scratch {
  uint8_t u[12 * STAGE];
  uint4 fix[8 * NREC * 12];
  uint32_t key[8 * NREC];
  uint32_t cnt[32];
  uint32_t launch[160];
  uint32_t tag[8];
};
__device__ __align__(128) Scratch g_scratch;
#define TS(slot, i)
#define TS1(slot, i)
#define TSS(slot, i)
#define TSDUMP(slot)

__device__ __forceinline__ float bf16lo(uint32_t v) { return __uint_as_float(v << 16); }
__device__ __forceinline__ float bf16hi(uint32_t v) { return __uint_as_float(v & 0xffff0000u); }
__device__ __forceinline__ uint32_t smem_u32(const void* p) { return (uint32_t)__cvta_generic_to_shared(p); }
__device__ __forceinline__ void mbar_init(uint32_t bar, uint32_t count) {
  asm volatile("mbarrier.init.shared::cta.b64 [%0], %1;\n" ::"r"(bar), "r"(count) : "memory");
}
__device__ __forceinline__ void mbar_expect_tx(uint32_t bar, uint32_t bytes) {
  asm volatile("mbarrier.arrive.expect_tx.shared::cta.b64 _, [%0], %1;\n" ::"r"(bar), "r"(bytes) : "memory");
}
__device__ __forceinline__ void mbar_wait(uint32_t bar, uint32_t parity = 0) {
  asm volatile(
      "{\n.reg .pred p;\n.reg .u32 n;\nmov.u32 n, 0;\n"
      "W_%=:\n"
      "mbarrier.try_wait.parity.shared::cta.b64 p, [%0], %1;\n"
      "@p bra D_%=;\n"
      "add.u32 n, n, 1;\nsetp.lt.u32 p, n, 0x1000000;\n@p bra W_%=;\ntrap;\n"
      "D_%=:\n}\n" ::"r"(bar), "r"(parity) : "memory");
}
__device__ __forceinline__ bool mbar_test(uint32_t bar) {
  uint32_t done;
  asm volatile(
      "{\n.reg .pred p;\n"
      "mbarrier.test_wait.parity.shared::cta.b64 p, [%1], 0;\n"
      "selp.u32 %0, 1, 0, p;\n}\n"
      : "=r"(done)
      : "r"(bar)
      : "memory");
  return __all_sync(0xffffffffu, done);
}
__device__ __forceinline__ void mbar_wait_cluster(uint32_t bar) {
  asm volatile(
      "{\n.reg .pred p;\n.reg .u32 n;\nmov.u32 n, 0;\n"
      "W_%=:\n"
      "mbarrier.try_wait.parity.shared::cta.b64 p, [%0], 0;\n"
      "@p bra D_%=;\n"
      "add.u32 n, n, 1;\nsetp.lt.u32 p, n, 0x1000000;\n@p bra W_%=;\ntrap;\n"
      "D_%=:\n}\n" ::"r"(bar) : "memory");
}
__device__ __forceinline__ uint32_t clock32() {
  uint32_t c;
  asm volatile("mov.u32 %0, %%clock;\n" : "=r"(c)::"memory");
  return c;
}
__device__ __forceinline__ int lane_now() {
  int l;
  asm volatile("mov.u32 %0, %%laneid;\n" : "=r"(l));
  return l;
}
__device__ __forceinline__ void wait_until(uint32_t t0, uint32_t dt) {
  while (clock32() - t0 < dt) __nanosleep(40);
}
__device__ __forceinline__ void tma_load_x(uint32_t dst, const CUtensorMap* tm, uint32_t bar, uint32_t bytes, int c0, int c1, int c2) {
  mbar_expect_tx(bar, bytes);
  asm volatile(
      "cp.async.bulk.tensor.3d.shared::cluster.global.mbarrier::complete_tx::bytes [%0], [%1, {%3, %4, %5}], [%2];\n" ::"r"(dst),
      "l"(reinterpret_cast<uint64_t>(tm)), "r"(bar), "r"(c0), "r"(c1), "r"(c2)
      : "memory");
}
__device__ __forceinline__ void tma_load_w(uint32_t dst, const CUtensorMap* tm, uint32_t bar, int c, int kj, int ki, uint32_t mask) {
  asm volatile(
      "cp.async.bulk.tensor.5d.shared::cluster.global.mbarrier::complete_tx::bytes.multicast::cluster [%0], [%1, {%3, %4, "
      "%3, %5, %6}], [%2], %7;\n" ::"r"(dst),
      "l"(reinterpret_cast<uint64_t>(tm)), "r"(bar), "r"(0), "r"(c), "r"(kj), "r"(ki), "h"((uint16_t)mask)
      : "memory");
}
__device__ __forceinline__ void bulk_load_mc(uint32_t dst, const void* src, uint32_t bytes, uint32_t bar) {
  asm volatile(
      "cp.async.bulk.shared::cluster.global.mbarrier::complete_tx::bytes.multicast::cluster [%0], [%1], %2, [%3], %4;\n" ::"r"(dst),
      "l"(src), "r"(bytes), "r"(bar), "h"((uint16_t)3)
      : "memory");
}
__device__ __forceinline__ void tma_store(const CUtensorMap* tm, uint32_t src, int c1, int c2, int c3) {
  asm volatile("cp.async.bulk.tensor.5d.global.shared::cta.bulk_group [%0, {%2, %3, %4, %5, %2}], [%1];\n" ::"l"(
                   reinterpret_cast<uint64_t>(tm)),
               "r"(src), "r"(0), "r"(c1), "r"(c2), "r"(c3)
               : "memory");
  asm volatile("cp.async.bulk.commit_group;\n" ::: "memory");
}
__device__ __forceinline__ constexpr uint64_t w_desc(uint32_t saddr) {
  return (uint64_t)((saddr & 0x3FFFF) >> 4) | ((uint64_t)(1024 >> 4) << 16) | ((uint64_t)(512 >> 4) << 32) | ((uint64_t)2 << 62);
}
__device__ __forceinline__ constexpr uint64_t a_desc(uint32_t saddr) {
  return (uint64_t)((saddr & 0x3FFFF) >> 4) | ((uint64_t)1 << 16) | ((uint64_t)(VROW >> 4) << 32) | ((uint64_t)2 << 62);
}
#define ACC_OPERANDS(c, d)                                                                                        \
  c(d[0]), c(d[1]), c(d[2]), c(d[3]), c(d[4]), c(d[5]), c(d[6]), c(d[7]), c(d[8]),      \
      c(d[9]), c(d[10]), c(d[11]), c(d[12]), c(d[13]), c(d[14]), c(d[15]), c(d[16]),       \
      c(d[17]), c(d[18]), c(d[19]), c(d[20]), c(d[21]), c(d[22]), c(d[23]), c(d[24]),      \
      c(d[25]), c(d[26]), c(d[27]), c(d[28]), c(d[29]), c(d[30]), c(d[31]), c(d[32]),      \
      c(d[33]), c(d[34]), c(d[35]), c(d[36]), c(d[37]), c(d[38]), c(d[39]), c(d[40]),      \
      c(d[41]), c(d[42]), c(d[43]), c(d[44]), c(d[45]), c(d[46]), c(d[47])
#define ACC_LIST                                                                   \
  "{%0, %1, %2, %3, %4, %5, %6, %7, %8, %9, %10, %11, %12, %13, %14, %15, "        \
  "%16, %17, %18, %19, %20, %21, %22, %23, %24, %25, %26, %27, %28, %29, %30, %31, " \
  "%32, %33, %34, %35, %36, %37, %38, %39, %40, %41, %42, %43, %44, %45, %46, %47}, "
__device__ __forceinline__ void wgmma_ss(float* d, uint64_t adesc, uint64_t bdesc, uint32_t accumulate) {
  asm volatile(
      "{\n.reg .pred p;\nsetp.ne.b32 p, %50, 0;\n"
      "wgmma.mma_async.sync.aligned.m64n96k16.f32.bf16.bf16 " ACC_LIST "%48, %49, p, 1, 1, 0, 1;\n}\n"
      : ACC_OPERANDS("+f", d)
      : "l"(adesc), "l"(bdesc), "r"(accumulate));
}
__device__ __forceinline__ void wgmma_def(float* d, uint64_t desc) {
  asm volatile(
      "{\n.reg .pred p;\nsetp.ne.b32 p, 0, 0;\n"
      "wgmma.mma_async.sync.aligned.m64n96k16.f32.bf16.bf16 " ACC_LIST "%48, %48, p, 1, 1, 1, 1;\n}\n"
      : ACC_OPERANDS("=f", d)
      : "l"(desc));
}
__device__ __forceinline__ void wgmma_rs(float* d, const uint32_t* a, uint64_t bdesc) {
  asm volatile(
      "{\n.reg .pred p;\nsetp.ne.b32 p, 1, 0;\n"
      "wgmma.mma_async.sync.aligned.m64n96k16.f32.bf16.bf16 " ACC_LIST "{%48, %49, %50, %51}, %52, p, 1, 1, 1;\n}\n"
      : ACC_OPERANDS("+f", d)
      : "r"(a[0]), "r"(a[1]), "r"(a[2]), "r"(a[3]), "l"(bdesc));
}
__device__ __forceinline__ void wgmma_fence() { asm volatile("wgmma.fence.sync.aligned;\n" ::: "memory"); }
__device__ __forceinline__ void wgmma_commit() { asm volatile("wgmma.commit_group.sync.aligned;\n" ::: "memory"); }
template <int N>
__device__ __forceinline__ void wgmma_wait() { asm volatile("wgmma.wait_group.sync.aligned %0;\n" ::"n"(N) : "memory"); }
__device__ __forceinline__ void acc_fence(float* d) {
#pragma unroll
  for (int i = 0; i < 48; i++) asm volatile("" : "+f"(d[i])::"memory");
}
#define UPD(text, d, e, c) asm volatile("{\n.reg .pred p;\nsetp.eq.u32 p, %3, 0;\n@p " text ";\n}\n" : "+f"(d) : "f"(e), "f"(c), "r"(guard))
#define UPD_ADD(d, e, c) UPD("fma.rn.f32 %0, %1, %2, %0", d, e, c)
#define UPD_MUL(d, e, c) UPD("fma.rn.f32 %0, %0, %2, %1", d, e, c)
#define UPD_SCL(d, c) UPD("mul.f32 %0, %0, %2", d, c, c)
__device__ __forceinline__ void keep_alive8(const uint32_t* a, uint32_t never) {
  asm volatile(
      "{\n.reg .pred p, q;\nsetp.eq.u32 p, %8, 16;\nsetp.eq.u32 q, %8, 32;\n"
      "@p st.shared.v4.b32 [%8], {%0, %1, %2, %3};\n@q st.shared.v4.b32 [%8], {%4, %5, %6, %7};\n}\n" ::"r"(a[0]),
      "r"(a[1]), "r"(a[2]), "r"(a[3]), "r"(a[4]), "r"(a[5]), "r"(a[6]), "r"(a[7]), "r"(never)
      : "memory");
}
__device__ __forceinline__ void ldsm4(uint32_t& r0, uint32_t& r1, uint32_t& r2, uint32_t& r3, uint32_t addr) {
  asm volatile("ldmatrix.sync.aligned.m8n8.x4.shared.b16 {%0, %1, %2, %3}, [%4];\n"
               : "=r"(r0), "=r"(r1), "=r"(r2), "=r"(r3)
               : "r"(addr)
               : "memory");
}
__device__ __forceinline__ void ldsm4(uint32_t* r, uint32_t addr) { ldsm4(r[0], r[1], r[2], r[3], addr); }
__device__ __forceinline__ void arrive_if(uint32_t bar) {
  asm volatile("{\n.reg .pred p;\nsetp.ne.u32 p, %0, 0;\n@p mbarrier.arrive.shared::cluster.b64 _, [%0];\n}\n" ::"r"(bar) : "memory");
}
__device__ __forceinline__ uint32_t lds32(uint32_t addr) {
  uint32_t v;
  asm volatile("ld.shared.u32 %0, [%1];\n" : "=r"(v) : "r"(addr) : "memory");
  return v;
}
__device__ __forceinline__ void lds64(uint32_t& a, uint32_t& b, uint32_t addr) {
  asm volatile("ld.shared.v2.u32 {%0, %1}, [%2];\n" : "=r"(a), "=r"(b) : "r"(addr) : "memory");
}
__device__ __forceinline__ void lds128(uint32_t* v, uint32_t addr) {
  asm volatile("ld.shared.v4.b32 {%0, %1, %2, %3}, [%4];\n" : "=r"(v[0]), "=r"(v[1]), "=r"(v[2]), "=r"(v[3]) : "r"(addr) : "memory");
}
__device__ __forceinline__ void sts128(uint32_t addr, const uint32_t* v) {
  asm volatile("st.shared.v4.b32 [%0], {%1, %2, %3, %4};\n" ::"r"(addr), "r"(v[0]), "r"(v[1]), "r"(v[2]), "r"(v[3]) : "memory");
}
__device__ __forceinline__ void sts64(uint32_t addr, const uint32_t* v) {
  asm volatile("st.shared.v2.b32 [%0], {%1, %2};\n" ::"r"(addr), "r"(v[0]), "r"(v[1]) : "memory");
}
__device__ __forceinline__ void sts32(uint32_t addr, uint32_t v) {
  asm volatile("st.shared.u32 [%0], %1;\n" ::"r"(addr), "r"(v) : "memory");
}
__device__ __forceinline__ void fence_async() { asm volatile("fence.proxy.async.shared::cta;\n" ::: "memory"); }
__device__ __forceinline__ void bar_sync(int id, int n) { asm volatile("bar.sync %0, %1;\n" ::"r"(id), "r"(n) : "memory"); }
__device__ __forceinline__ __nv_bfloat162 as_bf2(uint32_t v) { return *reinterpret_cast<__nv_bfloat162*>(&v); }
__device__ __forceinline__ uint32_t as_u32(__nv_bfloat162 v) { return *reinterpret_cast<uint32_t*>(&v); }
__device__ __forceinline__ uint32_t hfma2(uint32_t c, uint32_t a, uint32_t b) { return as_u32(__hfma2(as_bf2(c), as_bf2(a), as_bf2(b))); }
__device__ __forceinline__ uint32_t hadd2(uint32_t a, uint32_t b) { return as_u32(__hadd2(as_bf2(a), as_bf2(b))); }
__device__ __forceinline__ uint32_t hsub2(uint32_t a, uint32_t b) { return as_u32(__hsub2(as_bf2(a), as_bf2(b))); }
__device__ __forceinline__ __nv_bfloat162 half_of(uint32_t w, int hi) { return hi ? __high2bfloat162(as_bf2(w)) : __low2bfloat162(as_bf2(w)); }
__device__ __forceinline__ uint32_t hmul2_h(uint32_t w, int hi, uint32_t a) { return as_u32(__hmul2(half_of(w, hi), as_bf2(a))); }
__device__ __forceinline__ uint32_t hfma2_h(uint32_t w, int hi, uint32_t a, uint32_t c) {
  return as_u32(__hfma2(half_of(w, hi), as_bf2(a), as_bf2(c)));
}
__device__ __forceinline__ uint32_t pack2(float lo, float hi) { return as_u32(__floats2bfloat162_rn(lo, hi)); }
__device__ __forceinline__ uint32_t prmt(uint32_t a, uint32_t b, uint32_t sel) {
  uint32_t r;
  asm("prmt.b32 %0, %1, %2, %3;\n" : "=r"(r) : "r"(a), "r"(b), "r"(sel));
  return r;
}
__device__ __forceinline__ uint32_t clip2(uint32_t p) {
  return as_u32(__hmin2(__hmax2(as_bf2(p), as_bf2(0u)), as_bf2(0x435f435fu)));
}
__device__ __forceinline__ constexpr uint32_t tap_delta(int a, int b) {
  return (a == 0 ? 0xbf80u : a == 1 ? 0u : 0x3f80u) | (b == 0 ? 0xbf800000u : b == 1 ? 0u : 0x3f800000u);
}
__device__ __forceinline__ void coefs(uint32_t w, uint32_t& p0, uint32_t& p1) {
  const uint32_t o = hsub2(0x3f803f80u, w);
  const uint32_t xa = __byte_perm(o, w, 0x7632);
  p0 = hmul2_h(o, 0, xa);
  p1 = hmul2_h(w, 0, xa);
}
__device__ __forceinline__ uint32_t frac2(uint32_t pos) {
  const float py = bf16lo(pos), px = bf16hi(pos);
  return __byte_perm(__float_as_uint(py - floorf(py)), __float_as_uint(px - floorf(px)), 0x7632);
}
__device__ __forceinline__ void blend4(uint32_t* t, const uint32_t* g, const uint32_t* h, const uint32_t* k, uint32_t a0,
                                       uint32_t a1, uint32_t b0, uint32_t b1) {
#pragma unroll
  for (int i = 0; i < 4; i++) {
    const uint32_t p0 = (i & 1) ? b0 : a0, p1 = (i & 1) ? b1 : a1;
    t[i] = hfma2_h(p1, 1, k[i], hfma2_h(p1, 0, h[i], hfma2_h(p0, 1, g[i], hmul2_h(p0, 0, t[i]))));
  }
}
__device__ __forceinline__ bool elect_one() {
  uint32_t r;
  asm volatile("{\n.reg .pred p;\nelect.sync _|p, 0xffffffff;\nselp.u32 %0, 1, 0, p;\n}\n" : "=r"(r));
  return r != 0;
}

template <int N>
__device__ __forceinline__ void transform6(const uint32_t (*d)[N], uint32_t dst, uint32_t dst0) {
  uint32_t v[N], t[N], u[N];
  auto put = [&](int slot, const uint32_t* r) {
    const uint32_t a = slot < 4 ? dst + slot * VSLOT : dst0 + (slot - 4) * 3 * VSLOT;
    if (N == 4) sts128(a, r);
    else sts64(a, r);
  };
#pragma unroll
  for (int k = 0; k < 2; k++) {
#pragma unroll
    for (int i = 0; i < N; i++) v[i] = hfma2(0xc088c088u, d[2 + k][i], hadd2(d[k][i], d[4 + k][i]));
    put(4 + k, v);
  }
#pragma unroll
  for (int k = 0; k < 2; k++) {
    const uint32_t c = k ? 0xbe80be80u : 0xc080c080u, f = k ? 0x40004000u : 0x3f003f00u;
#pragma unroll
    for (int i = 0; i < N; i++) {
      t[i] = hfma2(c, d[2][i], d[4][i]);
      u[i] = hfma2(c, d[1][i], d[3][i]);
      v[i] = hfma2(f, u[i], t[i]);
    }
    put(2 * k, v);
#pragma unroll
    for (int i = 0; i < N; i++) t[i] = hfma2(f ^ 0x80008000u, u[i], t[i]);
    put(2 * k + 1, t);
  }
}

template <int GROUP = 4096>
__device__ __forceinline__ void stage_slab(const float* acc, uint32_t stg, int lane, int j0 = 0, int j1 = 6) {
  const uint32_t a = stg + (lane & 15) * 64 + (((lane >> 4) ^ ((lane >> 1) & 3)) << 4);
#pragma unroll
  for (int jp = j0; jp < j1; jp++) {
    uint32_t pk[4];
#pragma unroll
    for (int i = 0; i < 4; i++) pk[i] = pack2(acc[jp * 8 + i * 2], acc[jp * 8 + i * 2 + 1]);
    asm volatile("stmatrix.sync.aligned.m8n8.x4.shared.b16 [%0], {%1, %2, %3, %4};\n" ::"r"((a ^ ((jp & 1) * 32)) + (jp >> 1) * GROUP),
                 "r"(pk[0]), "r"(pk[1]), "r"(pk[2]), "r"(pk[3])
                 : "memory");
  }
}
__device__ __forceinline__ void publish(uint32_t bar, int lane) {
  fence_async();
  __syncwarp();
  arrive_if(lane == 0 ? bar : 0u);
}
__device__ __forceinline__ uint32_t w_stg(int wg, int i) {
  return i == 2 ? wg * 12288 : i == 1 ? (wg ? SM_WW + 2 * STAGE : 24576) : 4 * VSLOT + (i ? 24576 : 0) + wg * 12288;
}

__device__ __forceinline__ void ldsm4_if(uint32_t* r, uint32_t addr, uint32_t on) {
  asm volatile(
      "{\n.reg .pred p;\nsetp.ne.u32 p, %5, 0;\n"
      "@p ldmatrix.sync.aligned.m8n8.x4.shared.b16 {%0, %1, %2, %3}, [%4];\n}\n"
      : "+r"(r[0]), "+r"(r[1]), "+r"(r[2]), "+r"(r[3])
      : "r"(addr), "r"(on)
      : "memory");
}
__device__ __forceinline__ void push_record(uint32_t bars, uint32_t key, uint32_t pos) {
  uint32_t slot;
  asm volatile("atom.shared.add.u32 %0, [%1], 1;\n" : "=r"(slot) : "r"(bars + O_CNT) : "memory");
  const uint32_t v[2] = {key, pos};
  if (slot < NREC) sts64(bars + O_REC + slot * 8, v);
}
__device__ __noinline__ void push_taps(uint32_t bars, uint32_t key, uint32_t taps, const uint32_t* __restrict__ offs) {
  const int y = key & 255, x = (key >> 8) & 255;
#pragma unroll 1
  for (; taps; taps &= taps - 1) {
    const int tap = __ffs(taps) - 1, ki = (tap * 11) >> 5;
    const uint32_t gp = pack2((float)(y + ki - 1), (float)(x + tap - ki * 3 - 1));
    push_record(bars, key | (tap << 16), clip2(hadd2(gp, __ldg(offs + (y * IW + x) * 9 + tap))));
  }
}
__device__ __forceinline__ uint32_t wino_key(int y, int x) {
  return y | (x << 8) | ((((y & 28) << 1) | (x & 7)) << 20) | ((((x & 8) >> 1) | (y & 3)) << 27);
}
__device__ __forceinline__ uint32_t strip_key(int u, int v, int left) {
  return (left ? v | (u << 8) : u | (v << 8)) | ((((u & 15) << 3) | (v & 7)) << 20) | ((u >> 4) << 29);
}
__device__ __forceinline__ bool strip_off(uint32_t d, bool out) { return (d & 0x7fff) || (d & 0x7fff7fffu) > (out ? 0u : 0x3f000000u); }
__device__ __forceinline__ uint32_t delta(uint32_t key, uint32_t pos, const uint32_t* __restrict__ x, int c) {
  const int tap = (key >> 16) & 15, ki = (tap * 11) >> 5, gy = (int)bf16lo(pos), gx = (int)bf16hi(pos);
  const int cy = min(max((int)(key & 255) + ki - 1, 0), IH - 1), cx = min(max((int)((key >> 8) & 255) + tap - ki * 3 - 1, 0), IW - 1);
  const int sx = gx < IW - 1 ? 48 : 0, sy = gy < IH - 1 ? IW * 48 : 0;
  const uint32_t* pc = x + (gy * IW + gx) * 48 + c;
  uint32_t q0, q1;
  coefs(frac2(pos), q0, q1);
  const uint32_t v = hfma2_h(q1, 1, __ldg(pc + sy + sx), hfma2_h(q1, 0, __ldg(pc + sy), hfma2_h(q0, 1, __ldg(pc + sx), hmul2_h(q0, 0, __ldg(pc)))));
  return hsub2(v, __ldg(x + (cy * IW + cx) * 48 + c));
}
__device__ __forceinline__ void fixup(uint32_t bars, int w, int n0, int n1, const uint32_t* __restrict__ x, const uint4* __restrict__ wgt) {
  const uint32_t fix = bars + SM_FIX - SM_BAR, part = fix + NREC * 192;
#pragma unroll 1
  for (int r = n0; r < n1; r++) {
    uint32_t key, pos, d[4], sum[4];
    int l = lane_now();
    lds64(key, pos, bars + O_REC + r * 8);
    key = __shfl_sync(0xffffffffu, key, 0);
    pos = __shfl_sync(0xffffffffu, pos, 0);
    const int tap = (key >> 16) & 15;
    sts32(part + w * 192 + (l & 7) * 4, delta(key, pos, x, w * 8 + (l & 7)));
    __syncwarp();
    l = min(lane_now(), 23);
    const int up = l >= 12;
    const uint4* wp = wgt + (tap * 96 + w * 16 + up * 7) * 12 + l;
#pragma unroll
    for (int h = 0; h < 2; h++) {
      uint4 wv[4];
#pragma unroll
      for (int k = 0; k < 4; k++) wv[k] = __ldg(wp + (h * 4 + k) * 12);
      lds64(d[h * 2], d[h * 2 + 1], part + w * 192 + up * 16 + h * 8);
#pragma unroll
      for (int k = 0; k < 4; k++) {
#pragma unroll
        for (int i = 0; i < 4; i++)
          sum[i] = h + k == 0 ? hmul2_h(d[0], 0, (&wv[k].x)[i]) : hfma2_h(d[h * 2 + (k >> 1)], k & 1, (&wv[k].x)[i], sum[i]);
      }
      asm volatile("" : "+l"(wp));
    }
#pragma unroll
    for (int i = 0; i < 4; i++) sum[i] = hadd2(sum[i], __shfl_down_sync(0xffffffffu, sum[i], 12));
    l = lane_now();
    if (l < 12) sts128(part + w * 192 + l * 16, sum);
    bar_sync(4, 192);
    const int t = w * 8 + l;
    if (l < 8) {
      float lo = 0.0f, hi = 0.0f;
#pragma unroll
      for (int k = 0; k < 6; k++) {
        const uint32_t v = lds32(part + k * 192 + t * 4);
        lo += bf16lo(v);
        hi += bf16hi(v);
      }
      sts32(fix + r * 192 + t * 4, pack2(lo, hi));
    }
    bar_sync(4, 192);
  }
}
__device__ __forceinline__ void patch(uint32_t bars, uint32_t mask, uint32_t key, uint32_t stg, uint32_t group, int lane) {
#pragma unroll 1
  for (; mask; mask &= mask - 1) {
    const uint32_t r = __ffs(mask) - 1, m = (__shfl_sync(0xffffffffu, key, r) >> 20) & 127;
    if (lane < 24) {
      const uint32_t a = stg + (lane >> 3) * group + m * 64 + ((((lane ^ m) >> 1) & 3) << 4) + (lane & 1) * 8;
      uint32_t v[2], c[2];
      lds64(v[0], v[1], a);
      lds64(c[0], c[1], bars + SM_FIX - SM_BAR + r * 192 + lane * 8);
      v[0] = hadd2(v[0], c[0]);
      v[1] = hadd2(v[1], c[1]);
      sts64(a, v);
    }
    __syncwarp();
  }
  fence_async();
  __syncwarp();
}

struct Maps {
  CUtensorMap x[5];
  CUtensorMap w[2];
  CUtensorMap out[4];
};

__global__ void __cluster_dims__(2, 1, 1) __launch_bounds__(NTHREADS, 1)
dcn_kernel(const __nv_bfloat16* __restrict__ x, const uint32_t* __restrict__ offs, const uint4* __restrict__ wgt, Scratch* scr,
           const uint32_t never, const __grid_constant__ Maps tm) {
  extern __shared__ __align__(1024) uint8_t smem[];
  const uint32_t sbase = smem_u32(smem);
  const uint32_t bars = sbase + SM_BAR;
  const int tid = threadIdx.x;
  const int cta = blockIdx.x;
  const uint32_t tstart = clock32();
  const int wid = __shfl_sync(0xffffffffu, tid >> 5, 0);
  const int lane = tid & 31;
  const bool wino = cta < NW, strip = !wino && cta < NW + NG;
  const int left = cta >= NW + NG / 2;
  const int ry = (cta * 43) >> 9;
  const int x0 = wino ? 32 + (cta - ry * 12) * 16 : 32 + (cta - NW - left * (NG / 2)) * 8, y0 = 32 + ry * 32;
  auto load_piece = [&](int q) {
    tma_load_x(sbase + 4 * VSLOT + q * PIECE, &tm.x[0], bars + (B_XF + q) * 8, PIECE, 0, x0 - 1 + 2 * q, y0 - 1);
  };
  auto load_half = [&](int s, int hf) {
    tma_load_x(sbase + SM_R + hf * HALF, &tm.x[4], bars + (B_XF + 7 + s * 2 + hf) * 8, HALF, s * 32, x0 - 1, y0 - 1 + hf * 17);
  };
  auto task = [&](int q) {
    const int tp = lane >> 3, e = (lane >> 2) & 1;
    const uint32_t src = sbase + 4 * VSLOT + q * PIECE + tp * 1024 + (x0 + 2 * q == IW ? 0 : e * 64) + (lane & 3) * 16;
    const uint32_t last = y0 + 32 == IH && tp == 3 ? 8 * 128 : 9 * 128;
    const int h = tp * 18 + q;
    const uint32_t vb = sbase + h * 128 + e * 64;
    mbar_wait(bars + (B_XF + q) * 8);
    uint32_t d[10][4];
#pragma unroll
    for (int r = 0; r < 9; r++) lds128(d[r], src + r * 128);
    lds128(d[9], src + last);
    const uint32_t v0 = vb + (((lane ^ h) & 3) << 4), v1 = vb + VROW + (((lane ^ (h + 1)) & 3) << 4);
    transform6<4>(d, v0, v0 + 9 * VSLOT);
    transform6<4>(d + 4, v1, v1 + 9 * VSLOT);
    publish(bars + (B_VF + (q >= 5)) * 8, lane);
  };
  const bool prep = wid >= 8 && wid < 11 && !wino && cta < NW + 36;
  const int pkj = ((cta - NW) * 43) >> 9, pc8 = cta - NW - pkj * 12;
  int oy, ox;
  bool own = strip;
  {
    const int src = cta - NW - NG, t = tid & 127;
    int lf = left, pu = (tid >> 5) * 4 + (lane & 3), pv = x0 + (lane >> 2);
    if (!strip) {
      lf = src < 7 ? src >= 4 : t < 64;
      pu = 32 + (t & 1);
      pv = src < 4 ? 32 + src * 48 + (t >> 1) : src < 7 ? src * 64 - 224 + (t >> 1) : (t >> 1) & 31;
      own = src < 8 && tid >= 128 && (src < 4 ? t < 96 : src == 7 || pv >= 34);
    }
    oy = lf ? pv : pu;
    ox = lf ? pu : pv;
  }
  const bool one = elect_one();
  uint4 g[3];
  uint32_t o2[9];
  if (wid >= 12) {
    if (one) {
      if (wid == 15) {
#pragma unroll
        for (int i = 0; i < 13; i++) mbar_init(bars + (B_XF + i) * 8, 1);
        if (wino) {
#pragma unroll 1
          for (int q = 0; q < 5; q++) load_piece(q);
        }
      } else if (wid == 14) {
#pragma unroll
        for (int i = 0; i < 18; i++) mbar_init(bars + (B_WF + i) * 8, 1);
        const uint32_t z[4] = {0, 0, 0, 0};
        sts128(bars + O_TGT, z);
        __threadfence_block();
      } else if (wid == 13) {
#pragma unroll
        for (int i = 0; i < 15; i++) mbar_init(bars + (B_WE + i) * 8, i < 11 ? 16 : 8);
#pragma unroll
        for (int i = 0; i < 4; i++) mbar_init(bars + (B_VF + i) * 8, i == 0 ? 8 : i == 1 ? 4 : 6);
        mbar_init(bars + B_VE * 8, 8);
        mbar_init(bars + B_RE * 8, 6);
        mbar_init(bars + B_SC * 8, wino ? 7 : 9);
        mbar_init(bars + B_UI * 8, 1);
              } else {
#pragma unroll
        for (int i = 0; i < 8; i++) mbar_init(bars + (B_ST + i) * 8, 4);
#pragma unroll
        for (int i = 0; i < 15; i++) mbar_init(bars + (B_GF + i) * 8, 1);
      }
      asm volatile("fence.mbarrier_init.release.cluster;\n" ::: "memory");
    }
    __syncwarp();
  } else if (wid >= 8) {
    if (prep) {
      const uint4* src = wgt + ((cta - NW) * 8 + (lane >> 2)) * 12 + (wid - 8) * 4 + (lane & 3);
#pragma unroll
      for (int k = 0; k < 3; k++) g[k] = __ldg(src + k * 3456);
    }
  } else if (!wino) {
    if (strip) {
      if (one) wait_until(tstart, ODELAY);
      __syncwarp();
    }
    if (own) {
      const uint32_t* op = offs + (oy * IW + ox) * 9;
#pragma unroll
      for (int m = 0; m < 9; m++) o2[m] = __ldg(op + (strip && left ? m % 3 * 3 + m / 3 : m));
    }
  }
  auto load_cw = [&](int st) {
    uint32_t rank;
    asm volatile("mov.u32 %0, %%cluster_ctarank;\n" : "=r"(rank));
    const int g = (st * 11) >> 5;
    const uint32_t fb = bars + (B_GF + st) * 8;
    mbar_expect_tx(fb, STAGE);
    tma_load_w(sbase + st * STAGE, &tm.w[1], fb, g * 32, 0, st - g * 3, 1u << rank);
    tma_load_w(sbase + st * STAGE + STAGE / 2, &tm.w[1], fb, g * 32 + 16, 0, st - g * 3, 1u << rank);
  };
  auto load_cx = [&](int wg, int g, uint32_t tl) {
    tma_load_x(sbase + SM_CX + wg * CWIN + g * CSLICE, &tm.x[3], bars + (B_GX + wg * 3 + g) * 8, CSLICE, g * 32, (int)(tl & 255) * 8 - 2,
               (int)(tl >> 8) * 8 - 2);
  };
  auto corner_tile = [&](int wg) {
    const uint32_t t = ((wg ? 0xfbea00000000ull : 0xdc7398265410ull) >> (4 * (cta - NW - NG))) & 15;
    return (t & 3) | ((t >> 2) << 8);
  };
  asm volatile("barrier.cluster.arrive.relaxed.aligned;\n" ::: "memory");
    if (prep) {
      constexpr float NA = AL / (2 * PA * PA * (PA * PA - PB * PB)), NB = 1.0f / (2 * (PB * PB - PA * PA));
      uint32_t u[4][4];
#pragma unroll
      for (int i = 0; i < 4; i++) {
        float r[4][2];
#pragma unroll
        for (int h = 0; h < 2; h++) {
          const uint32_t w0 = (&g[0].x)[i], w1 = (&g[1].x)[i], w2 = (&g[2].x)[i];
          const float g0 = h ? bf16hi(w0) : bf16lo(w0), g1 = h ? bf16hi(w1) : bf16lo(w1), g2 = h ? bf16hi(w2) : bf16lo(w2);
          const float ea = fmaf(PA * PA, g2, g0) * NA, eb = fmaf(PB * PB, g2, g0) * NB;
          r[0][h] = fmaf(PA * NA, g1, ea);
          r[1][h] = fmaf(-PA * NA, g1, ea);
          r[2][h] = fmaf(PB * NB, g1, eb);
          r[3][h] = fmaf(-PB * NB, g1, eb);
        }
#pragma unroll
        for (int k = 0; k < 4; k++) u[k][i] = pack2(r[k][0], r[k][1]);
      }
      const uint32_t tmp = sbase + SM_FIX + (wid - 8) * 2048;
      TS(5, 17);
#pragma unroll
      for (int k = 0; k < 4; k++) sts128(tmp + k * 512 + (lane >> 2) * 64 + (((lane ^ (lane >> 3)) & 3) << 4), u[k]);
      fence_async();
      __syncwarp();
      TS(5, 18);
      if (one) {
        const uint8_t* dst = scr->u + (pc8 >> 2) * (4 * STAGE) + ((pc8 >> 1) & 1) * (STAGE / 2) + pkj * 3072 +
                             (wid - 8) * 1024 + (pc8 & 1) * 512;
#pragma unroll
        for (int k = 0; k < 4; k++)
          asm volatile("cp.async.bulk.global.shared::cta.bulk_group [%0], [%1], 512;\n" ::"l"(dst + k * STAGE), "r"(tmp + k * 512) : "memory");
        asm volatile("cp.async.bulk.commit_group;\n" ::: "memory");
        asm volatile("cp.async.bulk.wait_group 0;\n" ::: "memory");
        asm volatile("red.relaxed.gpu.global.add.u32 [%0], 1;\n" ::"l"(scr->cnt) : "memory");
        TS1(5, 21);
      }
      __syncwarp();
    }
  if (wid >= 8) {
    asm volatile("setmaxnreg.dec.sync.aligned.u32 32;\n");
    uint32_t launch;
    if (wid == 9 || wid == 14) launch = scr->launch[cta];
    asm volatile("barrier.cluster.wait.acquire.aligned;\n" ::: "memory");
    if (wid == 15) {
      if (one) {
        uint32_t rank;
        asm volatile("mov.u32 %0, %%cluster_ctarank;\n" : "=r"(rank));
        if (wino) {
          for (uint32_t spin = 0;; spin++) {
            uint32_t v;
            asm volatile("ld.volatile.shared.u32 %0, [%1];\n" : "=r"(v) : "r"(bars + O_TGT) : "memory");
            if (v) break;
            if (spin > (1u << 24)) __trap();
          }
          asm volatile("fence.proxy.async.global;\n" ::: "memory");
          TS1(6, 21);
          int slot = 0;
#pragma unroll 1
          for (int st = 0; st < 18; st++) {
            if (st >= 3 && (st < 12 || st >= 16)) mbar_wait_cluster(bars + (B_WE + st - (st < 12 ? 3 : 7)) * 8);
            const uint32_t fb = bars + (B_WF + st) * 8;
            const uint32_t dst = sbase + (st < 12 ? SM_WW + slot * STAGE : (st < 14 ? 4 * VSLOT : st < 16 ? SM_R : SM_WW) + (st & 1) * STAGE) + rank * (STAGE / 2);
            mbar_expect_tx(fb, STAGE);
            if (st < 12) {
              bulk_load_mc(dst, scr->u + st * STAGE + rank * (STAGE / 2), STAGE / 2, fb);
            } else {
              tma_load_w(dst, &tm.w[1], fb, slot * 32 + rank * 16, 0, st >= 15 ? 2 : 0, 3);
            }
            TS1(6, st);
            if (st == 2) arrive_if(bars + B_UI * 8);
            if (++slot == 3) slot = 0;
          }
        } else if (strip) {
#pragma unroll 1
          for (int st = 0; st < 9; st++) {
            const int g = (st * 11) >> 5, tv = st - g * 3;
            if (st == 8) mbar_wait_cluster(bars + B_WE * 8);
            else wait_until(tstart, GW0 + st * GWS);
            const uint32_t fb = bars + (B_WF + st) * 8;
            mbar_expect_tx(fb, STAGE);
            tma_load_w(sbase + SM_GW + (st & 7) * STAGE + rank * (STAGE / 2), &tm.w[left], fb, g * 32 + rank * 16, left ? 0 : tv,
                       left ? tv : 0, 3);
            TS1(6, st);
          }
        } else {
#pragma unroll 1
          for (int st = 0; st < 9; st++) {
            wait_until(tstart, CW0 + st * CWS);
            load_cw(st);
          }
        }
      }
      TSDUMP(6);
    } else if (wid == 14) {
      if (one) {
        if (wino) {
          wait_until(tstart, BDELAY);
#pragma unroll 1
          for (int q = 5; q < 9; q++) load_piece(q);
          mbar_wait(bars + B_UI * 8);
          wait_until(tstart, SDELAY);
          load_half(1, 0);
          wait_until(tstart, SDELAY + SDELAY2);
          load_half(1, 1);
          wait_until(tstart, FDELAY);
        } else {
#pragma unroll 1
          for (int k = 0; k < 6; k++) {
            const int wg = k & 1, g = k >> 1;
            wait_until(tstart, strip ? (wg ? GX1 : GX0) + g * GXS : CX0 + g * CXS);
            if (strip)
              tma_load_x(sbase + wg * GWIN + g * GSLICE, &tm.x[1 + left], bars + (B_XF + wg * 3 + g) * 8, GSLICE, g * 32, x0 - 1, wg * 16 - 2);
            else if (!wg || cta >= GRID - 4)
              load_cx(wg, g, corner_tile(wg));
          }
        }
      }
      bar_sync(6, 32);
      if (wino || strip) {
        const int lane = lane_now();
        if (wino) asm volatile("cp.async.bulk.prefetch.L2.global [%0], 576;\n" ::"l"(offs + ((y0 + lane) * IW + x0) * 9) : "memory");
        TS(5, 10);
        const uint32_t tag = launch + 1;
        uint32_t n = 0;
#pragma unroll 1
        for (int k = wino && y0 == 32 ? 0 : 1; k < (x0 == 32 ? 2 : 1); k++) {
          const int src = !wino ? 7 : k ? 4 + (ry >> 1) : (cta * 11) >> 5;
          uint32_t v;
          asm volatile(
              "{\n.reg .pred p;\n.reg .u32 n, t;\nmov.u32 n, 0;\n"
              "W_%=:\n"
              "ld.acquire.gpu.global.u32 %0, [%1];\nxor.b32 t, %0, %2;\nsetp.lt.u32 p, t, 256;\n"
              "@p bra D_%=;\n"
              "nanosleep.u32 200;\nadd.u32 n, n, 1;\nsetp.lt.u32 p, n, 0x100000;\n@p bra W_%=;\ntrap;\n"
              "D_%=:\n}\n"
              : "=r"(v)
              : "l"(scr->tag + src), "r"(tag << 8)
              : "memory");
          v &= 255;
          if (v > NREC) n = 99;
          const uint32_t key = __ldcg(scr->key + src * NREC + (lane & 15));
          const uint32_t dy = (key & 255) - (wino ? y0 : left ? 32 : 0), dx = ((key >> 8) & 255) - (wino || !left ? x0 : 0);
          uint32_t mask = __ballot_sync(0xffffffffu, lane < v && dy < 32 && dx < (left ? 32 : 16));
#pragma unroll 1
          for (; mask && n < NREC; mask &= mask - 1, n++) {
            const int r = __ffs(mask) - 1;
            if (lane < 12) {
              const uint4 e = __ldcg(scr->fix + (src * NREC + r) * 12 + lane);
              sts128(sbase + SM_FIX + (NREC - 1 - n) * 192 + lane * 16, &e.x);
            }
            if (lane == r) sts32(bars + O_REC + 128 + (NREC - 1 - n) * 4, key);
          }
          if (mask) n = 99;
        }
        if (lane == 0) sts32(bars + O_CNT + 4, n + (tag & never));
        __syncwarp();
        arrive_if(lane == 0 ? bars + B_SC * 8 : 0u);
        TS(5, 11);
        TSDUMP(5);
      }
    } else if (wino || strip) {
      if (wino) {
        int lane = lane_now();
        if (wid >= 10) {
          const int ty = (wid - 10) * 2 + (lane >> 4), h = ty * 9 + 4;
          const uint32_t src = sbase + 4 * VSLOT + 4 * PIECE + ty * 512 + (lane & 15) * 8;
          const uint32_t v0 = sbase + h * 128 + (lane & 8) * 8 + ((((lane >> 1) ^ h) & 3) << 4) + (lane & 1) * 8;
          mbar_wait(bars + (B_XF + 4) * 8);
          uint32_t d[6][2];
#pragma unroll
          for (int r = 0; r < 5; r++) lds64(d[r][0], d[r][1], src + r * 128);
          lds64(d[5][0], d[5][1], src + (y0 + 4 * ty + 4 == IH ? 4 : 5) * 128);
          transform6<2>(d, v0, v0 + 9 * VSLOT);
          publish(bars + B_VF * 8, lane);
        }
        if (wid == 9) {
          const uint32_t target = (launch + 1) * 108;
          if (one) {
            wait_until(tstart, PDELAY + (cta & 1) * PSTEP);
            asm volatile(
                "{\n.reg .pred p;\n.reg .u32 n, v;\nmov.u32 n, 0;\n"
                "W_%=:\n"
                "ld.relaxed.gpu.global.u32 v, [%0];\nsub.u32 v, v, %1;\nsetp.ge.s32 p, v, 0;\n"
                "@p bra D_%=;\n"
                "add.u32 n, n, 1;\nsetp.lt.u32 p, n, 0x400000;\n@p bra W_%=;\ntrap;\n"
                "D_%=:\n"
                "mapa.shared::cluster.u32 v, %2, 0;\nst.volatile.shared::cluster.u32 [v], %3;\n"
                "mapa.shared::cluster.u32 v, %2, 1;\nst.volatile.shared::cluster.u32 [v], %3;\n}\n" ::"l"(scr->cnt),
                "r"(target), "r"(bars + O_TGT), "r"(1)
                : "memory");
            TS(5, 0);
          }
          __syncwarp();
        }
        bar_sync(4, 192);
        const int i0 = (wid - 8) * 4 + (lane >> 3);
        const uint32_t v0 = sbase + i0 * 64 + ((((lane >> 1) ^ (i0 >> 1)) & 3) << 4) + (lane & 1) * 8;
#pragma unroll 1
        for (int s = 1; s < 3; s++) {
          mbar_wait(bars + (B_XF + 7 + s * 2) * 8);
          if (s == 1) {
            mbar_wait(bars + B_VF * 8);
            mbar_wait(bars + (B_VF + 1) * 8);
          } else {
            mbar_wait(bars + B_VE * 8);
          }
          if (wid < 11) TS(wid - 6, s * 4);
#pragma unroll 2
          for (int j = 0; j < 6; j++) {
            if (j == 2) {

              mbar_wait(bars + (B_XF + 8 + s * 2) * 8);
            }
            if (wid == 8 && !(j & 1)) TS(7, s * 8 - 8 + j);
            const int i = i0 + j * 24, ty = (i * 57) >> 10;
            const uint32_t src = sbase + SM_R + ty * (3 * VROW) + min(i, ty * 18 + IW - x0) * 64 + (lane & 7) * 8;
            uint32_t d[6][2];
#pragma unroll
            for (int r = 0; r < 5; r++) lds64(d[r][0], d[r][1], src + r * VROW);
            lds64(d[5][0], d[5][1], src + (y0 + 4 * ty + 4 == IH ? 4 : 5) * VROW);
            transform6<2>(d, v0 + (s & 1) * 4 * VSLOT + j * 1536, v0 + (6 + 2 * s) * VSLOT + j * 1536);
            if (j == 3 && s == 1) {
              if (wid == 8) {
                bar_sync(5, 192);
                if (one) load_half(2, 0);
                __syncwarp();
              } else {
                asm volatile("bar.arrive 5, 192;\n" ::: "memory");
              }
            }
          }
          if (wid < 11) TS(wid - 6, s * 4 + 1);
          publish(bars + (B_VF + 1 + s) * 8, !one);
          if (wid < 11) TS(wid - 6, s * 4 + 2);
          if (wid == 8 && s == 1) {
            mbar_wait(bars + (B_VF + 2) * 8);
            if (one) load_half(2, 1);
            __syncwarp();
          }
        }
        const int t = (wid - 8) * 32 + lane_now(), row = (t * 171) >> 10;
        const uint4* op = reinterpret_cast<const uint4*>(offs + (y0 * IW + x0) * 9) + row * (IW * 9 / 4 - 6) + t;
        uint4 v[6];
#pragma unroll
        for (int k = 0; k < 6; k++) v[k] = __ldg(op + k * 6);
        __nv_bfloat162 mx = as_bf2(0u);
#pragma unroll
        for (int k = 0; k < 6; k++)
          mx = __hmax2_nan(mx, __hmax2_nan(__hmax2_nan(__habs2(as_bf2(v[k].x)), __habs2(as_bf2(v[k].y))),
                                           __hmax2_nan(__habs2(as_bf2(v[k].z)), __habs2(as_bf2(v[k].w)))));
        const uint32_t lim = (pack2((float)max(y0, 34) - 1.5f, (float)max(x0, 34) - 1.5f) & 0x7f807f80u) - 0x04000400u;
        uint32_t who = __ballot_sync(0xffffffffu, (as_u32(mx) & 0xffffu) >= (lim & 0xffffu) || (as_u32(mx) >> 16) >= (lim >> 16));
#pragma unroll 1
        for (; who; who &= who - 1) {
          const int k = lane_now(), q = (wid - 8) * 32 + __ffs(who) - 1, r = (q * 171) >> 10;
          const int wd = (q - r * 6 + (k >> 2) * 6) * 4 + (k & 3), c = (wd * 57) >> 9, tap = wd - c * 9, ki = (tap * 11) >> 5;
          const int y = y0 + r, xx = x0 + c;
          if (k < 24 && min(y, xx) >= 34) {
            const uint32_t gp = pack2((float)(y + ki - 1), (float)(xx + tap - ki * 3 - 1));
            const uint32_t pos = clip2(hadd2(gp, __ldg(offs + (y * IW + xx) * 9 + tap)));
            if (pos != clip2(gp)) push_record(bars, wino_key(y, xx) | (tap << 16), pos);
          }
          __syncwarp();
        }
        arrive_if(one ? bars + B_SC * 8 : 0u);
        if (wid == 8) TS(7, 20);
      }
      if (wid < 10 && one)
        asm volatile("prefetch.tensormap [%0];\n" ::"l"(reinterpret_cast<uint64_t>(&tm.out[wino ? 0 : 1 + left])) : "memory");
      mbar_wait(bars + B_SC * 8);
      if (wid == 10 && one) atomicAdd(scr->launch + cta, 1);
      uint32_t n0, n1;
      lds64(n0, n1, bars + O_CNT);
      n0 = __shfl_sync(0xffffffffu, n0, 0);
      n1 = __shfl_sync(0xffffffffu, n1, 0);
      if (n0 + n1 <= NREC) fixup(bars, wid - 8, 0, n0, reinterpret_cast<const uint32_t*>(x), wgt);
      lds64(n0, n1, bars + O_CNT);
      const int lane = lane_now();
      if (wid < 10 && __all_sync(0xffffffffu, n0 + n1 <= NREC)) {
        const int wg = wid - 8;
        const uint32_t key = lds32(bars + O_REC + (lane < n0 ? lane * 8 : 128 + (lane & 15) * 4));
#pragma unroll 1
        for (int k = 0; k < (wino ? 4 : 1); k++) {
          const int i = wino ? (2 - k) & 3 : 0;
          const uint32_t stg = sbase + (wino ? w_stg(wg, i) : wg * GWIN);
          const uint32_t mask = __ballot_sync(0xffffffffu, (lane < n0 || (lane < NREC && lane + n1 >= NREC)) && key >> 27 == wg * 4 + i);
          mbar_wait(bars + (B_ST + wg * 4 + i) * 8);
          if (mask) patch(bars, mask, key, stg, wino ? 4096 : 8192, lane);
          if (one) tma_store(&tm.out[wino ? 0 : 1 + left], stg, x0 + (wino ? wg * 8 : 0), wino ? i : wg * 16, wino ? y0 >> 2 : 0);
          TS1(wid - 6, 20 + k);
        }
        asm volatile("cp.async.bulk.wait_group.read 0;\n" ::: "memory");
        TS1(wid - 6, 24);
      }
      if (wid < 11) TSDUMP(wid - 6);
      if (wid == 8) TSDUMP(7);
    }
  } else {
    const int wg = wid >> 2, warp = wid & 3;
    if ((sbase & 0xffffff) != SB) __trap();
    asm volatile("setmaxnreg.inc.sync.aligned.u32 224;\n");
    asm volatile("barrier.cluster.wait.acquire.aligned;\n" ::: "memory");
    uint32_t we_addr;
    {
      uint32_t rank;
      asm volatile("mov.u32 %0, %%cluster_ctarank;\n" : "=r"(rank));
      asm volatile("mapa.shared::cluster.u32 %0, %1, %2;\n" : "=r"(we_addr) : "r"(bars + B_WE * 8), "r"(rank ^ (uint32_t)(lane & 1)));
      if (lane >= 2) we_addr = 0;
    }
    const uint32_t nv = never & (uint32_t)tid;
    float acc[4][48];
    int ntiles = 0;
    uint32_t tile0 = 0, tstep = 0;
    if (wino) {
      TSS(wg, 23);
      task(wid + wg);
      TSS(wg, 24);
      constexpr uint64_t bd0 = w_desc(SB);
      const uint64_t ad0 = a_desc(SB) + wg * 32;
      uint32_t rel = 0;
      if (lane == 2) we_addr = bars + (B_VE - 3) * 8;
      uint32_t guard = never;
      auto stage = [&](float* a, int st, int rs, int vslot, uint32_t accumulate, auto work) {
        const uint64_t bd = bd0 + (rs >> 4), ad = ad0 + vslot * (VSLOT >> 4);
        mbar_wait(bars + (B_WF + st) * 8);
        TSS(wg, st);
        wgmma_fence();
#pragma unroll
        for (int j = 0; j < 6; j++) {
          wgmma_ss(a, ad + (j >> 1) * 4 + (j & 1) * 2, bd + (j >> 1) * WTAP + (j & 1) * WHALF, j ? 1 : accumulate);
          if (j == 1) {
            wgmma_commit();
            wgmma_wait<1>();
            arrive_if(rel);
            rel = st < 15 && (lane < (st < 11 ? 2 : 1) || (lane == 2 && st == 3)) ? we_addr + st * 8 : 0u;
          }
          if (j == 5) wgmma_commit();
          work(j);
        }
      };
#pragma unroll
      for (int p = 0; p < 4; p++) {
        wgmma_fence();
        wgmma_def(acc[p], bd0);
      }
      wgmma_commit();
      mbar_wait(bars + B_VF * 8);
      mbar_wait(bars + (B_VF + wg) * 8);
      int rs = SM_WW;
#pragma unroll 1
      for (int s = 0;; s++) {
#pragma unroll
        for (int p = 0; p < 4; p++) {
          if (p == 2 && s == 2) goto last;
          stage(acc[p], s * 4 + p, rs, (s & 1) * 4 + p, s, [](int) {});
          rs = rs == SM_WW + 2 * STAGE ? SM_WW : rs + STAGE;
        }
        if (!mbar_test(bars + (B_VF + 2 + s) * 8)) {
          wgmma_wait<0>();
          arrive_if(rel);
          rel = 0;
          mbar_wait(bars + (B_VF + 2 + s) * 8);
        }
      }
    last:
      auto pin = [&] { if (PIN) guard = clock32() & never; };
      auto pq = [&](int i0, int i1) {
        pin();
#pragma unroll
        for (int i = i0; i < i1; i++) {
          UPD_ADD(acc[0][i], acc[1][i], 1.0f);
          UPD_MUL(acc[1][i], acc[0][i], -2.0f);
        }
      };
      stage(acc[2], 10, SM_WW + STAGE, 2, 1, [&](int j) { if (j) pq(j * 4 - 4, j * 4); });
      stage(acc[3], 11, SM_WW + 2 * STAGE, 3, 1, [&](int j) { pq(20 + j * 5, j < 5 ? 25 + j * 5 : 48); });
      wgmma_wait<0>();
      arrive_if(rel);
      rel = 0;
      TSS(wg, 18);
#pragma unroll
      for (int i = 0; i < 48; i++) {
        UPD_ADD(acc[2][i], acc[3][i], 1.0f);
        UPD_MUL(acc[3][i], acc[2][i], -2.0f);
        UPD_ADD(acc[2][i], acc[0][i], PA * PA / AL);
        UPD_ADD(acc[0][i], acc[2][i], 1.0f / (PB * PB));
      }
      const uint32_t stg = sbase + warp * 1024, stb = bars + (B_ST + wg * 4) * 8;
      auto odd = [&](int k) {
        pin();
#pragma unroll
        for (int i = k * 4; i < k * 4 + 4; i++) {
          UPD_ADD(acc[3][i], acc[1][i], PA * PA * PA / (AL * PB));
          acc[1][i] = fmaf(acc[1][i], (PA * PB - PA * PA * PA / PB) / AL, acc[3][i]) * (1.0f / PB);
          UPD_SCL(acc[3][i], PB);
        }
        if (k & 1) stage_slab(acc[1], stg + w_stg(wg, 1), lane, k >> 1, (k >> 1) + 1);
      };
      stage(acc[0], 12, 4 * VSLOT, 9, 1, [&](int j) {
        if (j == 0) mbar_wait(bars + (B_WE + 11) * 8);
        stage_slab(acc[2], stg + w_stg(wg, 2), lane, j, j + 1);
      });
      stage(acc[0], 13, 4 * VSLOT + STAGE, 8, 1, [&](int j) {
        if (j == 1) publish(stb + 16, lane);
        odd(j);
      });
      stage(acc[0], 14, SM_R, 10, 1, [&](int j) { odd(6 + j); });
      stage(acc[3], 15, SM_R + STAGE, 12, 1, [&](int j) {
        if (j == 1) publish(stb + 8, lane);
        if (j == 2) mbar_wait(bars + (B_WE + 13) * 8);
        if (j == 3) acc_fence(acc[0]);
        if (j >= 3) stage_slab(acc[0], stg + w_stg(wg, 0), lane, j * 2 - 6, j * 2 - 4);
      });
      stage(acc[3], 16, SM_WW, 11, 1, [&](int j) {
        if (j == 1) publish(stb, lane);
      });
      stage(acc[3], 17, SM_WW + STAGE, 13, 1, [&](int j) {
        if (j == 0) mbar_wait(bars + (B_WE + 14) * 8);
      });
      wgmma_wait<0>();
      acc_fence(acc[3]);
      TSS(wg, 20);
      stage_slab(acc[3], stg + w_stg(wg, 3), lane);
      publish(stb + 24, lane);
      TSS(wg, 21);
      mbar_wait(bars + B_SC * 8);
      if (lds32(bars + O_CNT) + lds32(bars + O_CNT + 4) > NREC) {
        ntiles = 4;
        tile0 = (x0 >> 3) + wg + (y0 << 5);
        tstep = 0x100;
      }
    } else if (strip) {
      uint32_t dl[4][9];
      {
        const int pu = wg * 16 + warp * 4 + (lane & 3), pv = x0 + (lane >> 2);
        const uint32_t base = pack2((float)pv, (float)pu), swap = left ? 0x3210u : 0x1032u;
        uint32_t bad = 0;
#pragma unroll
        for (int m = 0; m < 9; m++) {
          const uint32_t gp = hadd2(base, tap_delta(m % 3, m / 3)), cg = clip2(gp);
          uint32_t d = hsub2(clip2(hadd2(gp, __byte_perm(o2[m], 0, swap))), cg);
          const bool out = m < 3 && pu == 0, off = strip_off(d, out);
          bad |= off ? (1u << m) | (0x200u << (m % 3 * 3 + m / 3)) : 0u;
          d = out ? 0x3f800000u : off ? 0u : d & 0xffff0000u;
          d |= (int)d < 0 ? 0x7654u : 0x3210u;
#pragma unroll
          for (int r = 0; r < 4; r++) dl[r][m] = __shfl_sync(0xffffffffu, d, r, 4);
        }
        if (bad && pv >= 34) push_taps(bars, strip_key(pu, pv, left), left ? bad >> 9 : bad & 511, offs);
        __syncwarp();
        arrive_if(lane == 0 ? bars + B_SC * 8 : 0u);
      }
#pragma unroll
      for (int i = 0; i < 48; i++) acc[0][i] = acc[1][i] = 0.0f;
      uint32_t la[3];
#pragma unroll
      for (int tv = 0; tv < 3; tv++) {
        const int p = (warp * 4 + ((lane >> 3) & 1)) * 10 + min((lane & 7) + tv, IW - x0);
        la[tv] = sbase + wg * GWIN + p * 64 + ((((lane >> 4) ^ (p >> 1)) & 3) << 4);
      }
      uint32_t D[2][8][2], A[3][8];
#pragma unroll
      for (int i = 0; i < 24; i++) A[0][i] = nv;
      auto fetch = [&](int b, uint32_t a) {
#pragma unroll
        for (int i = 0; i < FETCHN; i++) ldsm4(D[b][2 * i][0], D[b][2 * i + 1][0], D[b][2 * i][1], D[b][2 * i + 1][1], (a ^ (((i + b) & 1) * 32)) + i * 2 * GROW);
      };
      TSS(wg, 23);
      mbar_wait(bars + (B_XF + wg * 3) * 8);
      fetch(0, la[0]);
      TSS(wg, 24);
#pragma unroll 1
      for (int g = 0; g < 3; g++) {
#pragma unroll
        for (int tv = 0; tv < 3; tv++) {
          const uint64_t bd = w_desc(SB + SM_GW) + (((g * 3 + tv) & 7) * (STAGE >> 4));
          mbar_wait(bars + (B_WF + g * 3 + tv) * 8);
          TSS(wg, g * 3 + tv);
#pragma unroll
          for (int kh = 0; kh < 2; kh++) {
            if (kh == 0) {
              fetch(1, la[tv] + g * GSLICE);
            } else if (tv < 2) {
              fetch(0, la[tv + 1] + g * GSLICE);
            } else {
              const int gn = min(g + 1, 2);
              mbar_wait(bars + (B_XF + wg * 3 + gn) * 8);
              fetch(0, la[0] + gn * GSLICE);
            }
            uint32_t E[7][2];
#pragma unroll
            for (int tu = 0; tu < 3; tu++) {
              wgmma_wait<2>();
              keep_alive8(A[tu], nv);
              if (tv == 1 && kh == 1 && tu == 0) arrive_if(g == 0 ? we_addr : 0u);
#pragma unroll
              for (int i = 0; i < 8; i++) {
                const int r = (i >> 2) * 2 + (i & 1), h = (i >> 1) & 1;
                if (tu == 0 && r == 0) E[0][h] = hsub2(D[kh][1][h], D[kh][0][h]);
                if (tu == 0 || r == 3) E[r + tu + 1][h] = hsub2(D[kh][r + tu + 2][h], D[kh][r + tu + 1][h]);
                const uint32_t c = dl[r][tu * 3 + tv];
                A[tu][i] = hfma2_h(c, 1, prmt(E[r + tu + 1][h], E[r + tu][h], c), D[kh][r + tu + 1][h]);
                if ((i & 3) == 3) {
                  wgmma_fence();
                  wgmma_rs(acc[i >> 2], A[tu] + (i & 4), bd + tu * WTAP + kh * WHALF);
                }
              }
              wgmma_commit();
            }
          }
        }
      }
      wgmma_wait<0>();
#pragma unroll
      for (int i = 0; i < 3; i++) keep_alive8(A[i], nv);
      acc_fence(acc[0]);
      acc_fence(acc[1]);
      TSS(wg, 20);
      bar_sync(1 + wg, 128);
      const uint32_t stg = sbase + wg * GWIN + warp * 2048;
      stage_slab<8192>(acc[0], stg, lane);
      stage_slab<8192>(acc[1], stg + 1024, lane);
      publish(bars + (B_ST + wg * 4) * 8, lane);
      TSS(wg, 21);
      mbar_wait(bars + B_SC * 8);
      if (lds32(bars + O_CNT) + lds32(bars + O_CNT + 4) > NREC) {
        ntiles = 2;
        tile0 = left ? wg * 2 + (x0 << 5) : (x0 >> 3) + (wg << 9);
        tstep = left ? 1 : 0x100;
      }
    } else {
      ntiles = !wg || cta >= GRID - 4;
      tile0 = corner_tile(wg);
      if (!ntiles) {
        const int src = cta - NW - NG, t = tid & 127;
        const uint32_t tag = scr->launch[cta] + 1;
        if (own) {
          const int lf = src < 7 ? src >= 4 : t < 64, along = lf ? oy : ox;
          const uint32_t base = pack2((float)oy, (float)ox);
          uint32_t bad = 0;
#pragma unroll
          for (int m = 0; m < 9; m++) {
            const uint32_t gp = hadd2(base, tap_delta(m / 3, m % 3));
            const uint32_t d = hsub2(clip2(hadd2(gp, o2[m])), clip2(gp));
            bad |= strip_off(lf ? __byte_perm(d, 0, 0x1032) : d, src < 7 || (along == 0 && (lf ? m < 3 : m % 3 == 0))) ? 1u << m : 0u;
          }
          if (bad) push_taps(bars, src < 7 ? wino_key(oy, ox) : strip_key(along, 32 + (t & 1), !lf), bad, offs);
        }
        bar_sync(2, 128);
        TSS(wg, 0);
        const int n = __shfl_sync(0xffffffffu, lds32(bars + O_CNT), 0);
        if (n && n <= NREC) {
          const uint32_t tmp = sbase + SM_CX + CWIN;
#pragma unroll 2
          for (int i = t; i < n * 48; i += 128) {
            const int r = (i * 1366) >> 16;
            uint32_t key, pos;
            lds64(key, pos, bars + O_REC + r * 8);
            sts32(tmp + r * 16 + i * 4, delta(key, pos, reinterpret_cast<const uint32_t*>(x), i - r * 48));
          }
          bar_sync(2, 128);
          const int r0 = warp ? 99 : lane >> 2;
          const uint32_t k0 = lds32(bars + O_REC + (lane >> 2) * 8), k1 = lds32(bars + O_REC + 64 + (lane >> 2) * 8);
          const uint32_t t0 = r0 < n ? (k0 >> 16) & 15 : 15, t1 = r0 + 8 < n ? (k1 >> 16) & 15 : 15;
          const uint32_t taps = __reduce_or_sync(0xffffffffu, lane < n ? 1u << ((lds32(bars + O_REC + (lane & 15) * 8) >> 16) & 15) : 0u);
          uint32_t D[6][4];
#pragma unroll
          for (int k = 0; k < 6; k++) ldsm4(D[k], tmp + (lane & 15) * 208 + (lane >> 4) * 16 + k * 32);
#pragma unroll
          for (int i = 0; i < 48; i++) acc[0][i] = 0.0f;
          mbar_wait(bars + (B_GF + 6) * 8);
#pragma unroll 1
          for (uint32_t m = taps; m; m &= m - 1) {
            const uint32_t tap = __ffs(m) - 1, ki = (tap * 11) >> 5;
            uint32_t A[6][4];
#pragma unroll
            for (int k = 0; k < 6; k++) {
#pragma unroll
              for (int i = 0; i < 4; i++) A[k][i] = (i & 1 ? t1 : t0) == tap ? D[k][i] : 0u;
            }
#pragma unroll
            for (int g = 0; g < 3; g++) mbar_wait(bars + (B_GF + g * 3 + ki) * 8);
            wgmma_fence();
#pragma unroll
            for (int k = 0; k < 6; k++)
              wgmma_rs(acc[0], A[k], w_desc(SB) + ((k >> 1) * 3 + ki) * (STAGE >> 4) + (tap - ki * 3) * WTAP + (k & 1) * WHALF);
            wgmma_commit();
            wgmma_wait<0>();
#pragma unroll
            for (int k = 0; k < 3; k++) keep_alive8(A[2 * k], nv);
          }
          acc_fence(acc[0]);
          uint32_t* dst = reinterpret_cast<uint32_t*>(scr->fix) + (src * NREC + (lane >> 2)) * 48 + (lane & 3);
#pragma unroll
          for (int j = 0; j < 12; j++) {
            if (r0 < n) dst[j * 4] = pack2(acc[0][j * 4], acc[0][j * 4 + 1]);
            if (r0 + 8 < n) dst[j * 4 + 384] = pack2(acc[0][j * 4 + 2], acc[0][j * 4 + 3]);
          }
          if (!warp) scr->key[src * NREC + (lane >> 2) + (lane & 1) * 8] = lane & 1 ? k1 : k0;
        }
        TSS(wg, 1);
        __syncwarp();
        if (t == 0) {
          scr->launch[cta] = tag;
          asm volatile("st.release.gpu.global.u32 [%0], %1;\n" ::"l"(scr->tag + src), "r"((tag << 8) | min(n, 99)) : "memory");
        }
        TSS(wg, 2);
      }
    }
    if (ntiles) {
      const uint32_t winb = sbase + SM_CX + wg * CWIN, tab = sbase + SM_CT + wid * 1152;
      const uint32_t ck = (uint32_t)(lane >> 4) << 4;
      if (tstep) {
        bar_sync(3, 256);
        if (wid == 0 && one) {
#pragma unroll 1
          for (int st = 0; st < 9; st++) load_cw(st);
        }
        __syncwarp();
      }
#pragma unroll 1
      for (int n = 0; n < ntiles; n++) {
        const uint32_t tl = tile0 + n * tstep;
        const int wx0 = (int)(tl & 255) * 8 - 2, wy0 = (int)(tl >> 8) * 8 - 2;
        if (tstep && warp == 0 && one) {
#pragma unroll 1
          for (int g = 0; g < 3; g++) load_cx(wg, g, tl);
        }
        __syncwarp();
        uint32_t mout = 0, need = 0;
        {
          const int ph = wy0 + 2 + 2 * warp + ((lane >> 3) & 1), pw = wx0 + 2 + (lane & 7);
          uint32_t of[5];
#pragma unroll
          for (int k = 0; k < 5; k++) of[k] = __ldg(offs + (ph * IW + pw) * 9 + min((lane >> 4) + 2 * k, 8));
#pragma unroll 1
          for (int m = lane >> 4; m < 9; m += 2) {
            const int ki = (m * 11) >> 5;
            const uint32_t pos = clip2(hadd2(pack2((float)(ph + ki - 1), (float)(pw + m - ki * 3 - 1)), of[0]));
#pragma unroll
            for (int k = 0; k < 4; k++) of[k] = of[k + 1];
            const uint32_t iy = (int)bf16lo(pos) - wy0, ix = (int)bf16hi(pos) - wx0, f = frac2(pos);
            mout |= max(iy, ix) > 10 ? 1u << m : 0u;
            need |= ((f >> 16 ? 1u : 0u) | (f & 0xffffu ? 0x200u : 0u) | (f >> 16 && f & 0xffffu ? 0x40000u : 0u)) << m;
            const uint32_t pp = (iy * 12 + ix) * 0x10001u + 0x10000u;
            sts32(tab + m * 64 + (lane & 7) * 8 + ((lane >> 1) & 4), pos);
            sts32(tab + 576 + m * 64 + (lane & 15) * 4, pp * 64 + ((pp << 3) & 0x300030u));
          }
          mout = __reduce_or_sync(0xffffffffu, mout);
          need = __reduce_or_sync(0xffffffffu, need);
        }
        uint32_t outside;
        asm volatile("{\n.reg .pred p, q;\nsetp.ne.u32 p, %1, 0;\nbarrier.red.or.pred q, %2, 128, p;\nselp.u32 %0, 1, 0, q;\n}\n"
                     : "=r"(outside) : "r"(mout), "r"(1 + wg) : "memory");
        outside = __shfl_sync(0xffffffffu, outside, 0);
#pragma unroll
        for (int i = 0; i < 48; i++) acc[0][i] = 0.0f;
        if (!outside) {
          uint32_t T[3][4], C[2][3][4];
#pragma unroll
          for (int i = 0; i < 12; i++) T[0][i] = C[0][0][i] = C[1][0][i] = nv;
          auto fetch = [&](int k, uint32_t e, uint32_t slice, uint32_t nd) {
            e ^= ck * 0x10001u ^ (k & 1 ? 0x200020u : 0u);
            const uint32_t a0 = (e & 0xffffu) + slice, a1 = (e >> 16) + slice;
            ldsm4_if(T[k % 3], a0, never ^ 1);
            ldsm4_if(C[k & 1][0], a1, nd & 1);
            ldsm4_if(C[k & 1][1], (a0 + CROW) ^ 32, nd & 0x200u);
            ldsm4_if(C[k & 1][2], (a1 + CROW) ^ 32, nd & 0x40000u);
          };
          uint32_t ent[4], slice = winb;
          ent[0] = lds32(tab + 576 + (lane & 15) * 4);
          mbar_wait(bars + (B_GX + wg * 3) * 8, n & 1);
          fetch(0, ent[0], slice, need);
          int ki = 0, g = 0;
#pragma unroll 1
          for (int st = 0; st < 9; st++) {
            const uint64_t bd = w_desc(SB) + st * (STAGE >> 4);
            const int kn = ki == 2 ? 0 : ki + 1;
            uint32_t cf[3][4];
#pragma unroll
            for (int j = 0; j < 3; j++) {
              uint32_t wA, wB;
              lds64(wA, wB, tab + (ki * 3 + j) * 64 + (lane >> 2) * 8);
              ent[j + 1] = lds32(tab + 576 + (j < 2 ? ki * 3 + j + 1 : kn * 3) * 64 + (lane & 15) * 4);
              coefs(frac2(wA), cf[j][0], cf[j][1]);
              coefs(frac2(wB), cf[j][2], cf[j][3]);
            }
            mbar_wait(bars + (B_GF + st) * 8);
            TSS(wg, st);
#pragma unroll
            for (int k = 0; k < 6; k++) {
              wgmma_wait<1>();
              if (k == 5 && kn == 0 && g < 2) {
                g++;
                slice += CSLICE;
                mbar_wait(bars + (B_GX + wg * 3 + g) * 8, n & 1);
              }
              fetch(k + 1, ent[(k + 1) >> 1], slice, need >> (k < 5 ? ki * 3 + ((k + 1) >> 1) : kn * 3));
              blend4(T[k % 3], C[k & 1][0], C[k & 1][1], C[k & 1][2], cf[k >> 1][0], cf[k >> 1][1], cf[k >> 1][2], cf[k >> 1][3]);
              wgmma_fence();
              wgmma_rs(acc[0], T[k % 3], bd + (k >> 1) * WTAP + (k & 1) * WHALF);
              wgmma_commit();
            }
            ent[0] = ent[3];
            ki = kn;
          }
          wgmma_wait<0>();
          keep_alive8(T[0], nv);
          keep_alive8(T[1], nv);
        } else {
        uint32_t buf[2][8];
#pragma unroll
        for (int i = 0; i < 16; i++) buf[0][i] = nv;
        const uint32_t tmp = tab + 576 + lane * 16;
        int tap = 0, g = 0;
#pragma unroll 1
        for (int d = 0;; d += 2) {
#pragma unroll
          for (int b = 0; b < 2; b++) {
            const int k = d + b, q = (k * 11) >> 5;
            if (k == 27) goto tile_done;
            mbar_wait(bars + (B_GX + wg * 3 + g) * 8, n & 1);
            mbar_wait(bars + (B_GF + q) * 8);
            if (k == q * 3) TSS(wg, q);
            const uint32_t pos = lds32(tab + tap * 64 + (lane & 7) * 8 + ((lane >> 1) & 4));
            const int gy = (int)bf16lo(pos), gx = (int)bf16hi(pos);
            uint32_t T[8];
            if (!((mout >> tap) & 1)) {
              uint32_t wA, wB, pA0, pA1, pB0, pB1, G[4], H[4], K[4];
              lds64(wA, wB, tab + tap * 64 + (lane >> 2) * 8);
              const uint32_t slice = winb + g * CSLICE;
              const uint32_t p = (gy - wy0) * 12 + gx - wx0, p1 = p + 1;
              const uint32_t a00 = slice + p * 64 + (((p << 3) & 0x30) ^ ck), a01 = slice + p1 * 64 + (((p1 << 3) & 0x30) ^ ck);
              coefs(frac2(wA), pA0, pA1);
              coefs(frac2(wB), pB0, pB1);
#pragma unroll
              for (int hf = 0; hf < 2; hf++) {
                ldsm4(T + hf * 4, a00 ^ (hf * 32));
                ldsm4(G, a01 ^ (hf * 32));
                ldsm4(H, (a00 + CROW) ^ (hf * 32) ^ 32);
                ldsm4(K, (a01 + CROW) ^ (hf * 32) ^ 32);
                blend4(T + hf * 4, G, H, K, pA0, pA1, pB0, pB1);
              }
            } else {
              uint32_t q0, q1;
              coefs(frac2(pos), q0, q1);
              const int sx = gx < IW - 1 ? IC / 8 : 0, sy = gy < IH - 1 ? IW * IC / 8 : 0;
              const uint4* pc = reinterpret_cast<const uint4*>(x) + (gy * IW + gx) * (IC / 8) + g * 4 + (lane >> 4);
#pragma unroll
              for (int hf = 0; hf < 2; hf++) {
                uint4 v[4];
                v[0] = __ldg(pc + hf * 2);
                v[1] = __ldg(pc + hf * 2 + sx);
                v[2] = __ldg(pc + hf * 2 + sy);
                v[3] = __ldg(pc + hf * 2 + sy + sx);
                blend4(&v[0].x, &v[1].x, &v[2].x, &v[3].x, q0, q1, q0, q1);
                __syncwarp();
                sts128(tmp, &v[0].x);
                __syncwarp();
                ldsm4(T + hf * 4, tmp);
              }
            }
            wgmma_wait<1>();
            keep_alive8(buf[b], nv);
#pragma unroll
            for (int i = 0; i < 8; i++) asm volatile("xor.b32 %0, %1, %2;\n" : "=r"(buf[b][i]) : "r"(T[i]), "r"(nv));
            const uint64_t bd = w_desc(SB) + q * (STAGE >> 4) + (k - q * 3) * WTAP;
            wgmma_fence();
            wgmma_rs(acc[0], buf[b], bd);
            wgmma_rs(acc[0], buf[b] + 4, bd + WHALF);
            wgmma_commit();
            if (++tap == 9) {
              tap = 0;
              g++;
            }
          }
        }
      tile_done:
        wgmma_wait<0>();
        keep_alive8(buf[0], nv);
        keep_alive8(buf[1], nv);
        }
        acc_fence(acc[0]);
        TSS(wg, 20);
        bar_sync(1 + wg, 128);
        stage_slab(acc[0], winb + warp * 1024, lane);
        fence_async();
        bar_sync(1 + wg, 128);
        if (warp == 0 && one) {
          tma_store(&tm.out[3], winb, wx0 + 2, wy0 + 2, 0);
          asm volatile("cp.async.bulk.wait_group.read 0;\n" ::: "memory");
        }
        TSS(wg, 21);
      }
    }
    if (warp == 0) TSDUMP(wg);
  }
}

typedef CUresult (*EncodeTiledFn)(CUtensorMap*, CUtensorMapDataType, cuuint32_t, void*, const cuuint64_t*,
                                  const cuuint64_t*, const cuuint32_t*, const cuuint32_t*, CUtensorMapInterleave,
                                  CUtensorMapSwizzle, CUtensorMapL2promotion, CUtensorMapFloatOOBfill);

}

extern "C" void kernel_launch(void* const* d_in, const int* in_sizes, int n_in, void* d_out, int out_size) {
  static EncodeTiledFn encode = nullptr;
  static void* scratch = nullptr;
  if (!encode) {
    cudaGetSymbolAddress(&scratch, g_scratch);
    void* fn = nullptr;
    cudaDriverEntryPointQueryResult qres;
    cudaGetDriverEntryPoint("cuTensorMapEncodeTiled", &fn, cudaEnableDefault, &qres);
    encode = (EncodeTiledFn)fn;
    cudaFuncSetAttribute(dcn_kernel, cudaFuncAttributeMaxDynamicSharedMemorySize, SMEM_BYTES);
  }
  Maps tm;
  const cuuint32_t es[5] = {1, 1, 1, 1, 1};
  constexpr cuuint64_t PX = IC * 2, ROW = IW * IC * 2;
  for (int i = 0; i < 5; i++) {
    const cuuint64_t dims[3] = {IC, IW, IH};
    const cuuint64_t strides[2] = {i == 2 ? ROW : PX, i == 2 ? PX : ROW};
    const cuuint32_t box[5][3] = {{32, 2, 34}, {32, 10, 20}, {32, 10, 20}, {32, 12, 12}, {32, 18, 17}};
    encode(&tm.x[i], CU_TENSOR_MAP_DATA_TYPE_BFLOAT16, 3, d_in[0], dims, strides, box[i], es, CU_TENSOR_MAP_INTERLEAVE_NONE,
           i & 3 ? CU_TENSOR_MAP_SWIZZLE_64B : CU_TENSOR_MAP_SWIZZLE_NONE, CU_TENSOR_MAP_L2_PROMOTION_NONE,
           CU_TENSOR_MAP_FLOAT_OOB_FILL_NONE);
  }
  for (int i = 0; i < 2; i++) {
    const cuuint64_t dims[5] = {32, IC, 3, 3, 3};
    const cuuint64_t strides[4] = {IC * 2, 64, IC * IC * 2, 3 * IC * IC * 2};
    const cuuint32_t box[5] = {32, 16, 3, i ? 3u : 1u, i ? 1u : 3u};
    encode(&tm.w[i], CU_TENSOR_MAP_DATA_TYPE_BFLOAT16, 5, d_in[2], dims, strides, box, es, CU_TENSOR_MAP_INTERLEAVE_NONE,
           CU_TENSOR_MAP_SWIZZLE_64B, CU_TENSOR_MAP_L2_PROMOTION_L2_128B, CU_TENSOR_MAP_FLOAT_OOB_FILL_NONE);
  }
  for (int i = 0; i < 4; i++) {
    const cuuint64_t dims[5] = {32, IW, i ? IH : 4u, i ? 1u : IH / 4, 3};
    const cuuint64_t strides[4] = {i == 2 ? ROW : PX, i == 2 ? PX : ROW, 4 * ROW, 64};
    const cuuint32_t box[5] = {32, 8, i == 3 ? 8u : i ? 16u : 1u, i ? 1u : 8u, 3};
    encode(&tm.out[i], CU_TENSOR_MAP_DATA_TYPE_BFLOAT16, 5, d_out, dims, strides, box, es, CU_TENSOR_MAP_INTERLEAVE_NONE,
           CU_TENSOR_MAP_SWIZZLE_64B, CU_TENSOR_MAP_L2_PROMOTION_NONE, CU_TENSOR_MAP_FLOAT_OOB_FILL_NONE);
  }
  dcn_kernel<<<GRID, NTHREADS, SMEM_BYTES>>>((const __nv_bfloat16*)d_in[0], (const uint32_t*)d_in[1], (const uint4*)d_in[2],
                                             (Scratch*)scratch, 0u, tm);
}
```

```cpp
#include <cuda_runtime.h>
#include <cuda.h>
#include <cuda_bf16.h>
#include <stdint.h>

namespace {

constexpr int IH = 224, IW = 224, IC = 96;
constexpr int GRID = 132, NW = 72, NG = 48;
constexpr int NTHREADS = 512;
constexpr int STAGE = 18432;
constexpr int WTAP = 3072 >> 4, WHALF = (STAGE / 2) >> 4;
constexpr uint32_t SB = 0x400;
constexpr int VROW = 18 * 64, VSLOT = 8 * VROW, PIECE = 34 * 128;
constexpr int SM_R = 14 * VSLOT, SM_WW = SM_R + 39936;
constexpr int GROW = 10 * 64, GSLICE = 20 * GROW, GWIN = 3 * GSLICE, SM_GW = 2 * GWIN, SM_GO = SM_GW + 7 * STAGE, SM_GT = SM_GO + 9216;
constexpr int CROW = 12 * 64, CSLICE = 12 * CROW, CWIN = 3 * CSLICE, SM_CX = 9 * STAGE, SM_CT = SM_CX + 2 * CWIN;
constexpr int SM_FIX = 224256, SM_BAR = 231168, SMEM_BYTES = 232448;
constexpr int B_XF = 0, B_PP = 15, B_WF = 16, B_IM = 34, B_OF = 35, B_SR = 36, B_W2 = 96, B_OG = 7;
constexpr int B_WE = 40;
constexpr int B_WL = 56, B_V0 = 57, B_SG = 58, B_VE = 59;
constexpr int B_ST = 64, B_VF = 71, B_SW = 79, B_RE = 80, B_R2 = 85;
constexpr int O_TGT = 768, O_CNT = 776, O_REC = 784, O_TS = 1024;
constexpr int NREC = 16;
#define FP32T 0
#define BDELAY 1500
#define SDELAY 2600
#define FETCHN 4
#define BLENDN 3
#define PDELAY 4000
#define HOLD 0
#define SDELAY2 500
#define SWAIT 1
#define ODELAY 600
#define NPOLL 4
#define PSTEP 250
#define PF1 0
#define PF2 6000
#define PFS 500
#define PIN 1
#define FDELAY 8000
#define CW0 1500
#define CWS 500
#define CX0 1000
#define CXS 2500
#define BWAIT 1
#define UIST 0
#define PF0 0
#define ODDB 6
#define PQN 3
#define PPJ 0
#define CHUNK 4
#define NA0 5
#define WBOTH 1
#define LAFTER 0
#define XPRE 0
#define O1J 2
#define NS1 2
#define CPRED 0
#define GO0 1900
#define UDIRECT 0
#define UREL 0
#define XDELAY 0
#define SAFE 0
#define O0K 1
#define ADEF 1
#define WF32 0
#define GX0 2500
#define GX1 2900
#define GXS 2600
#define GW0 2700
#define GWS 900
constexpr float PA = FP32T ? 2.0f / 3.0f : 0.5f, PB = FP32T ? 1.5f : 2.0f;
constexpr float AL = 1.0f - PA * PA / (PB * PB);

struct Scratch {
  uint8_t u[8 * STAGE];
  uint4 fix[8 * NREC * 12];
  uint2 key[8 * NREC];
  uint32_t cnt[32];
  uint32_t launch[160];
};
__device__ __align__(128) Scratch g_scratch;
#define TS(slot, i)
#define TS1(slot, i)
#define TSS(slot, i)
#define TSDUMP(slot)

__device__ __forceinline__ float bf16lo(uint32_t v) { return __uint_as_float(v << 16); }
__device__ __forceinline__ float bf16hi(uint32_t v) { return __uint_as_float(v & 0xffff0000u); }
__device__ __forceinline__ uint32_t smem_u32(const void* p) { return (uint32_t)__cvta_generic_to_shared(p); }
__device__ __forceinline__ void mbar_init(uint32_t bar, uint32_t count) {
  asm volatile("mbarrier.init.shared::cta.b64 [%0], %1;\n" ::"r"(bar), "r"(count) : "memory");
}
__device__ __forceinline__ void mbar_expect_tx(uint32_t bar, uint32_t bytes) {
  asm volatile("mbarrier.arrive.expect_tx.shared::cta.b64 _, [%0], %1;\n" ::"r"(bar), "r"(bytes) : "memory");
}
__device__ __forceinline__ void mbar_wait(uint32_t bar, uint32_t parity = 0) {
  asm volatile(
      "{\n.reg .pred p;\n"
      "W_%=:\n"
      "mbarrier.try_wait.parity.shared::cta.b64 p, [%0], %1;\n"
      "@!p bra W_%=;\n}\n" ::"r"(bar), "r"(parity) : "memory");
}
__device__ __forceinline__ uint32_t mbar_poll(uint32_t bar) {
  uint32_t done;
  asm volatile(
      "{\n.reg .pred p;\n"
      "mbarrier.test_wait.parity.shared::cta.b64 p, [%1], 0;\n"
      "selp.u32 %0, 1, 0, p;\n}\n"
      : "=r"(done)
      : "r"(bar)
      : "memory");
  return done;
}
__device__ __forceinline__ bool mbar_test(uint32_t bar) {
  uint32_t done;
  asm volatile(
      "{\n.reg .pred p;\n"
      "mbarrier.test_wait.parity.shared::cta.b64 p, [%1], 0;\n"
      "selp.u32 %0, 1, 0, p;\n}\n"
      : "=r"(done)
      : "r"(bar)
      : "memory");
  return __all_sync(0xffffffffu, done);
}
__device__ __forceinline__ uint32_t clock32() {
  uint32_t c;
  asm volatile("mov.u32 %0, %%clock;\n" : "=r"(c)::"memory");
  return c;
}
__device__ __forceinline__ int lane_now() {
  int l;
  asm volatile("mov.u32 %0, %%laneid;\n" : "=r"(l));
  return l;
}
__device__ __forceinline__ void wait_until(uint32_t t0, uint32_t dt) {
  while (clock32() - t0 < dt) __nanosleep(40);
}
__device__ __forceinline__ void tma_load_x(uint32_t dst, const CUtensorMap* tm, uint32_t bar, uint32_t bytes, int c0, int c1, int c2) {
  if (bytes) mbar_expect_tx(bar, bytes);
  asm volatile(
      "cp.async.bulk.tensor.3d.shared::cluster.global.mbarrier::complete_tx::bytes [%0], [%1, {%3, %4, %5}], [%2];\n" ::"r"(dst),
      "l"(reinterpret_cast<uint64_t>(tm)), "r"(bar), "r"(c0), "r"(c1), "r"(c2)
      : "memory");
}
__device__ __forceinline__ void tma_load_x4(uint32_t dst, const CUtensorMap* tm, uint32_t bar, int c, int y, int pair) {
  asm volatile(
      "cp.async.bulk.tensor.4d.shared::cluster.global.mbarrier::complete_tx::bytes [%0], [%1, {%3, %6, %4, %5}], [%2];\n" ::"r"(dst),
      "l"(reinterpret_cast<uint64_t>(tm)), "r"(bar), "r"(c), "r"(y), "r"(pair), "r"(0)
      : "memory");
}
__device__ __forceinline__ void tma_load_o(uint32_t dst, const CUtensorMap* tm, uint32_t bar, int x, int y) {
  asm volatile(
      "cp.async.bulk.tensor.2d.shared::cluster.global.mbarrier::complete_tx::bytes [%0], [%1, {%3, %4}], [%2];\n" ::"r"(dst),
      "l"(reinterpret_cast<uint64_t>(tm)), "r"(bar), "r"(x * 9), "r"(y)
      : "memory");
}
__device__ __forceinline__ void tma_load_w(uint32_t dst, const CUtensorMap* tm, uint32_t bar, int c, int kj, int ki, uint32_t mask) {
  asm volatile(
      "cp.async.bulk.tensor.5d.shared::cluster.global.mbarrier::complete_tx::bytes.multicast::cluster [%0], [%1, {%3, %4, "
      "%3, %5, %6}], [%2], %7;\n" ::"r"(dst),
      "l"(reinterpret_cast<uint64_t>(tm)), "r"(bar), "r"(0), "r"(c), "r"(kj), "r"(ki), "h"((uint16_t)mask)
      : "memory");
}
__device__ __forceinline__ void bulk_load_mc(uint32_t dst, const void* src, uint32_t bytes, uint32_t bar) {
  asm volatile(
      "cp.async.bulk.shared::cluster.global.mbarrier::complete_tx::bytes.multicast::cluster [%0], [%1], %2, [%3], %4;\n" ::"r"(dst),
      "l"(src), "r"(bytes), "r"(bar), "h"((uint16_t)3)
      : "memory");
}
__device__ __forceinline__ void tma_store(const CUtensorMap* tm, uint32_t src, int c1, int c2, int c3) {
  asm volatile("cp.async.bulk.tensor.5d.global.shared::cta.bulk_group [%0, {%2, %3, %4, %5, %2}], [%1];\n" ::"l"(
                   reinterpret_cast<uint64_t>(tm)),
               "r"(src), "r"(0), "r"(c1), "r"(c2), "r"(c3)
               : "memory");
  asm volatile("cp.async.bulk.commit_group;\n" ::: "memory");
}
__device__ __forceinline__ constexpr uint64_t w_desc(uint32_t saddr) {
  return (uint64_t)((saddr & 0x3FFFF) >> 4) | ((uint64_t)(1024 >> 4) << 16) | ((uint64_t)(512 >> 4) << 32) | ((uint64_t)2 << 62);
}
__device__ __forceinline__ constexpr uint64_t a_desc(uint32_t saddr) {
  return (uint64_t)((saddr & 0x3FFFF) >> 4) | ((uint64_t)1 << 16) | ((uint64_t)(VROW >> 4) << 32) | ((uint64_t)2 << 62);
}
#define ACC_OPERANDS(c, d)                                                                                        \
  c(d[0]), c(d[1]), c(d[2]), c(d[3]), c(d[4]), c(d[5]), c(d[6]), c(d[7]), c(d[8]),      \
      c(d[9]), c(d[10]), c(d[11]), c(d[12]), c(d[13]), c(d[14]), c(d[15]), c(d[16]),       \
      c(d[17]), c(d[18]), c(d[19]), c(d[20]), c(d[21]), c(d[22]), c(d[23]), c(d[24]),      \
      c(d[25]), c(d[26]), c(d[27]), c(d[28]), c(d[29]), c(d[30]), c(d[31]), c(d[32]),      \
      c(d[33]), c(d[34]), c(d[35]), c(d[36]), c(d[37]), c(d[38]), c(d[39]), c(d[40]),      \
      c(d[41]), c(d[42]), c(d[43]), c(d[44]), c(d[45]), c(d[46]), c(d[47])
#define ACC_LIST                                                                   \
  "{%0, %1, %2, %3, %4, %5, %6, %7, %8, %9, %10, %11, %12, %13, %14, %15, "        \
  "%16, %17, %18, %19, %20, %21, %22, %23, %24, %25, %26, %27, %28, %29, %30, %31, " \
  "%32, %33, %34, %35, %36, %37, %38, %39, %40, %41, %42, %43, %44, %45, %46, %47}, "
__device__ __forceinline__ void wgmma_ss(float* d, uint64_t adesc, uint64_t bdesc, uint32_t accumulate) {
  asm volatile(
      "{\n.reg .pred p;\nsetp.ne.b32 p, %50, 0;\n"
      "wgmma.mma_async.sync.aligned.m64n96k16.f32.bf16.bf16 " ACC_LIST "%48, %49, p, 1, 1, 0, 1;\n}\n"
      : ACC_OPERANDS("+f", d)
      : "l"(adesc), "l"(bdesc), "r"(accumulate));
}
__device__ __forceinline__ void wgmma_def(float* d, uint64_t desc) {
  asm volatile(
      "{\n.reg .pred p;\nsetp.ne.b32 p, 0, 0;\n"
      "wgmma.mma_async.sync.aligned.m64n96k16.f32.bf16.bf16 " ACC_LIST "%48, %48, p, 1, 1, 1, 1;\n}\n"
      : ACC_OPERANDS("=f", d)
      : "l"(desc));
}
__device__ __forceinline__ void wgmma_rs(float* d, const uint32_t* a, uint64_t bdesc) {
  asm volatile(
      "{\n.reg .pred p;\nsetp.ne.b32 p, 1, 0;\n"
      "wgmma.mma_async.sync.aligned.m64n96k16.f32.bf16.bf16 " ACC_LIST "{%48, %49, %50, %51}, %52, p, 1, 1, 1;\n}\n"
      : ACC_OPERANDS("+f", d)
      : "r"(a[0]), "r"(a[1]), "r"(a[2]), "r"(a[3]), "l"(bdesc));
}
__device__ __forceinline__ void wgmma_fence() { asm volatile("wgmma.fence.sync.aligned;\n" ::: "memory"); }
__device__ __forceinline__ void wgmma_commit() { asm volatile("wgmma.commit_group.sync.aligned;\n" ::: "memory"); }
template <int N>
__device__ __forceinline__ void wgmma_wait() { asm volatile("wgmma.wait_group.sync.aligned %0;\n" ::"n"(N) : "memory"); }
__device__ __forceinline__ void acc_fence(float* d) {
#pragma unroll
  for (int i = 0; i < 48; i++) asm volatile("" : "+f"(d[i])::"memory");
}
#define UPD(text, d, e, c) asm volatile("{\n.reg .pred p;\nsetp.eq.u32 p, %3, 0;\n@p " text ";\n}\n" : "+f"(d) : "f"(e), "f"(c), "r"(guard))
#define UPD_ADD(d, e, c) UPD("fma.rn.f32 %0, %1, %2, %0", d, e, c)
#define UPD_MUL(d, e, c) UPD("fma.rn.f32 %0, %0, %2, %1", d, e, c)
#define UPD_SCL(d, c) UPD("mul.f32 %0, %0, %2", d, c, c)
__device__ __forceinline__ void keep_alive8(const uint32_t* a, uint32_t never) {
  asm volatile(
      "{\n.reg .pred p, q;\nsetp.eq.u32 p, %8, 16;\nsetp.eq.u32 q, %8, 32;\n"
      "@p st.shared.v4.b32 [%8], {%0, %1, %2, %3};\n@q st.shared.v4.b32 [%8], {%4, %5, %6, %7};\n}\n" ::"r"(a[0]),
      "r"(a[1]), "r"(a[2]), "r"(a[3]), "r"(a[4]), "r"(a[5]), "r"(a[6]), "r"(a[7]), "r"(never)
      : "memory");
}
__device__ __forceinline__ void ldsm4(uint32_t& r0, uint32_t& r1, uint32_t& r2, uint32_t& r3, uint32_t addr) {
  asm volatile("ldmatrix.sync.aligned.m8n8.x4.shared.b16 {%0, %1, %2, %3}, [%4];\n"
               : "=r"(r0), "=r"(r1), "=r"(r2), "=r"(r3)
               : "r"(addr)
               : "memory");
}
__device__ __forceinline__ void ldsm4(uint32_t* r, uint32_t addr) { ldsm4(r[0], r[1], r[2], r[3], addr); }
__device__ __forceinline__ void arrive_if(uint32_t bar) {
  asm volatile("{\n.reg .pred p;\nsetp.ne.u32 p, %0, 0;\n@p mbarrier.arrive.shared::cluster.b64 _, [%0];\n}\n" ::"r"(bar) : "memory");
}
__device__ __forceinline__ uint32_t lds32(uint32_t addr) {
  uint32_t v;
  asm volatile("ld.shared.u32 %0, [%1];\n" : "=r"(v) : "r"(addr) : "memory");
  return v;
}
__device__ __forceinline__ void lds64(uint32_t& a, uint32_t& b, uint32_t addr) {
  asm volatile("ld.shared.v2.u32 {%0, %1}, [%2];\n" : "=r"(a), "=r"(b) : "r"(addr) : "memory");
}
__device__ __forceinline__ void lds128(uint32_t* v, uint32_t addr) {
  asm volatile("ld.shared.v4.b32 {%0, %1, %2, %3}, [%4];\n" : "=r"(v[0]), "=r"(v[1]), "=r"(v[2]), "=r"(v[3]) : "r"(addr) : "memory");
}
__device__ __forceinline__ void sts128(uint32_t addr, const uint32_t* v) {
  asm volatile("st.shared.v4.b32 [%0], {%1, %2, %3, %4};\n" ::"r"(addr), "r"(v[0]), "r"(v[1]), "r"(v[2]), "r"(v[3]) : "memory");
}
__device__ __forceinline__ void sts64(uint32_t addr, const uint32_t* v) {
  asm volatile("st.shared.v2.b32 [%0], {%1, %2};\n" ::"r"(addr), "r"(v[0]), "r"(v[1]) : "memory");
}
__device__ __forceinline__ void sts32(uint32_t addr, uint32_t v) {
  asm volatile("st.shared.u32 [%0], %1;\n" ::"r"(addr), "r"(v) : "memory");
}
__device__ __forceinline__ void fence_async() { asm volatile("fence.proxy.async.shared::cta;\n" ::: "memory"); }
__device__ __forceinline__ void bar_sync(int id, int n) { asm volatile("bar.sync %0, %1;\n" ::"r"(id), "r"(n) : "memory"); }
__device__ __forceinline__ __nv_bfloat162 as_bf2(uint32_t v) { return *reinterpret_cast<__nv_bfloat162*>(&v); }
__device__ __forceinline__ uint32_t as_u32(__nv_bfloat162 v) { return *reinterpret_cast<uint32_t*>(&v); }
__device__ __forceinline__ uint32_t hfma2(uint32_t c, uint32_t a, uint32_t b) { return as_u32(__hfma2(as_bf2(c), as_bf2(a), as_bf2(b))); }
__device__ __forceinline__ uint32_t hadd2(uint32_t a, uint32_t b) { return as_u32(__hadd2(as_bf2(a), as_bf2(b))); }
__device__ __forceinline__ uint32_t hsub2(uint32_t a, uint32_t b) { return as_u32(__hsub2(as_bf2(a), as_bf2(b))); }
__device__ __forceinline__ __nv_bfloat162 half_of(uint32_t w, int hi) { return hi ? __high2bfloat162(as_bf2(w)) : __low2bfloat162(as_bf2(w)); }
__device__ __forceinline__ uint32_t hmul2_h(uint32_t w, int hi, uint32_t a) { return as_u32(__hmul2(half_of(w, hi), as_bf2(a))); }
__device__ __forceinline__ uint32_t hfma2_h(uint32_t w, int hi, uint32_t a, uint32_t c) {
  return as_u32(__hfma2(half_of(w, hi), as_bf2(a), as_bf2(c)));
}
__device__ __forceinline__ uint32_t pack2(float lo, float hi) { return as_u32(__floats2bfloat162_rn(lo, hi)); }
__device__ __forceinline__ uint32_t prmt(uint32_t a, uint32_t b, uint32_t sel) {
  uint32_t r;
  asm("prmt.b32 %0, %1, %2, %3;\n" : "=r"(r) : "r"(a), "r"(b), "r"(sel));
  return r;
}
__device__ __forceinline__ uint32_t clip2(uint32_t p) {
  return as_u32(__hmin2(__hmax2(as_bf2(p), as_bf2(0u)), as_bf2(0x435f435fu)));
}
__device__ __forceinline__ constexpr uint32_t tap_delta(int a, int b) {
  return (a == 0 ? 0xbf80u : a == 1 ? 0u : 0x3f80u) | (b == 0 ? 0xbf800000u : b == 1 ? 0u : 0x3f800000u);
}
__device__ __forceinline__ void coefs(uint32_t w, uint32_t& p0, uint32_t& p1) {
  const uint32_t o = hsub2(0x3f803f80u, w);
  const uint32_t xa = __byte_perm(o, w, 0x7632);
  p0 = hmul2_h(o, 0, xa);
  p1 = hmul2_h(w, 0, xa);
}
__device__ __forceinline__ uint32_t frac2(uint32_t pos) {
  const float py = bf16lo(pos), px = bf16hi(pos);
  return __byte_perm(__float_as_uint(py - floorf(py)), __float_as_uint(px - floorf(px)), 0x7632);
}
__device__ __forceinline__ void blend4(uint32_t* t, const uint32_t* g, const uint32_t* h, const uint32_t* k, uint32_t a0,
                                       uint32_t a1, uint32_t b0, uint32_t b1) {
#pragma unroll
  for (int i = 0; i < 4; i++) {
    const uint32_t p0 = (i & 1) ? b0 : a0, p1 = (i & 1) ? b1 : a1;
    t[i] = hfma2_h(p1, 1, k[i], hfma2_h(p1, 0, h[i], hfma2_h(p0, 1, g[i], hmul2_h(p0, 0, t[i]))));
  }
}
__device__ __forceinline__ bool elect_one() {
  uint32_t r;
  asm volatile("{\n.reg .pred p;\nelect.sync _|p, 0xffffffff;\nselp.u32 %0, 1, 0, p;\n}\n" : "=r"(r));
  return r != 0;
}

template <int N>
__device__ __forceinline__ void transform6(const uint32_t (*d)[N], uint32_t dst, uint32_t off0) {
  uint32_t v[N], t[N], u[N];
  auto put = [&](int slot, const uint32_t* r) {
    const uint32_t a = slot < 4 ? dst + slot * VSLOT : dst + off0 + (slot - 4) * VSLOT;
    if (N == 4) sts128(a, r);
    else sts64(a, r);
  };
#pragma unroll
  for (int k = 0; k < 2; k++) {
#pragma unroll
    for (int i = 0; i < N; i++) v[i] = hfma2(0xc088c088u, d[2 + k][i], hadd2(d[k][i], d[4 + k][i]));
    put(4 + k, v);
  }
#pragma unroll
  for (int k = 0; k < 2; k++) {
    const uint32_t c = k ? 0xbe80be80u : 0xc080c080u, f = k ? 0x40004000u : 0x3f003f00u;
#pragma unroll
    for (int i = 0; i < N; i++) {
      t[i] = hfma2(c, d[2][i], d[4][i]);
      u[i] = hfma2(c, d[1][i], d[3][i]);
      v[i] = hfma2(f, u[i], t[i]);
    }
    put(2 * k, v);
#pragma unroll
    for (int i = 0; i < N; i++) t[i] = hfma2(f ^ 0x80008000u, u[i], t[i]);
    put(2 * k + 1, t);
  }
}

__device__ __forceinline__ void weights4(const uint32_t* g0, const uint32_t* g1, const uint32_t* g2, uint32_t (*u)[4]) {
#pragma unroll
  for (int i = 0; i < 4; i++) {
    const uint32_t ea = hfma2(0xbe00be00u, g2[i], as_u32(__hmul2(as_bf2(g0[i]), as_bf2(0xbf00bf00u)))), eb = hfma2(0x3e803e80u, g0[i], g2[i]);
    u[0][i] = hfma2(0xbe80be80u, g1[i], ea);
    u[1][i] = hfma2(0x3e803e80u, g1[i], ea);
    u[2][i] = hfma2(0x3f003f00u, g1[i], eb);
    u[3][i] = hfma2(0xbf00bf00u, g1[i], eb);
  }
}

template <int GROUP = 4096, bool SCALE = false>
__device__ __forceinline__ void stage_slab(const float* acc, uint32_t stg, int lane, int j0 = 0, int j1 = 6) {
  const uint32_t a = stg + (lane & 15) * 64 + (((lane >> 4) ^ ((lane >> 1) & 3)) << 4);
#pragma unroll
  for (int jp = j0; jp < j1; jp++) {
    uint32_t pk[4];
#pragma unroll
    for (int i = 0; i < 4; i++) {
      constexpr float f = SCALE ? 8.0f / 15.0f : 1.0f;
      pk[i] = pack2(acc[jp * 8 + i * 2] * f, acc[jp * 8 + i * 2 + 1] * f);
    }
    asm volatile("stmatrix.sync.aligned.m8n8.x4.shared.b16 [%0], {%1, %2, %3, %4};\n" ::"r"((a ^ ((jp & 1) * 32)) + (jp >> 1) * GROUP),
                 "r"(pk[0]), "r"(pk[1]), "r"(pk[2]), "r"(pk[3])
                 : "memory");
  }
}
__device__ __forceinline__ void publish(uint32_t bar, int lane) {
  fence_async();
  __syncwarp();
  arrive_if(lane == 0 ? bar : 0u);
}
__device__ __forceinline__ constexpr uint32_t w_slot(int st) {
  return st < 3 ? SM_WW + st * STAGE : st == 3 ? 12 * VSLOT : st < 11 ? SM_WW + (st - 4) % 3 * STAGE : st < 13 ? 4 * VSLOT + (st - 11) * STAGE
         : st < 16 ? SM_WW + st % 3 * STAGE : st == 16 ? 4 * VSLOT : STAGE;
}
__device__ __forceinline__ constexpr uint64_t w_slots(int st0, int step, int n) {
  uint64_t r = 0;
  for (int i = 0; i < n; i++) r |= (uint64_t)(w_slot(st0 + i * step) >> 10) << (8 * i);
  return r;
}
__device__ __forceinline__ uint32_t w_stg(int wg, int i) {
  return wg ? (i == 2 ? SM_R + 24576 : i == 1 ? 0 : i == 0 ? 4 * VSLOT + STAGE : SM_WW + STAGE) : SM_R + (i & 1) * 12288;
}

__device__ __forceinline__ void ldsm4_if(uint32_t* r, uint32_t addr, uint32_t on) {
  asm volatile(
      "{\n.reg .pred p;\nsetp.ne.u32 p, %5, 0;\n"
      "@p ldmatrix.sync.aligned.m8n8.x4.shared.b16 {%0, %1, %2, %3}, [%4];\n}\n"
      : "+r"(r[0]), "+r"(r[1]), "+r"(r[2]), "+r"(r[3])
      : "r"(addr), "r"(on)
      : "memory");
}
__device__ __forceinline__ void push_record(uint32_t bars, uint32_t key, uint32_t pos) {
  uint32_t slot;
  asm volatile("atom.shared.add.u32 %0, [%1], 1;\n" : "=r"(slot) : "r"(bars + O_CNT) : "memory");
  const uint32_t v[2] = {key, pos};
  if (slot < NREC) sts64(bars + O_REC + slot * 8, v);
}
__device__ __noinline__ void push_taps(uint32_t bars, uint32_t key, uint32_t taps, const uint32_t* __restrict__ offs) {
  const int y = key & 255, x = (key >> 8) & 255;
#pragma unroll 1
  for (; taps; taps &= taps - 1) {
    const int tap = __ffs(taps) - 1, ki = (tap * 11) >> 5;
    const uint32_t gp = pack2((float)(y + ki - 1), (float)(x + tap - ki * 3 - 1));
    push_record(bars, key | (tap << 16), clip2(hadd2(gp, __ldg(offs + (y * IW + x) * 9 + tap))));
  }
}
__device__ __forceinline__ uint32_t wino_key(int y, int x) {
  return y | (x << 8) | ((((y & 28) << 1) | (x & 7)) << 20) | ((((x & 8) >> 1) | (y & 3)) << 27);
}
__device__ __forceinline__ uint32_t strip_key(int u, int v, int left) {
  return (left ? v | (u << 8) : u | (v << 8)) | ((((u & 15) << 3) | (v & 7)) << 20) | ((u >> 4) << 29);
}
__device__ __forceinline__ bool strip_off(uint32_t d, bool out) { return (d & 0x7fff) || (d & 0x7fff7fffu) > (out ? 0u : 0x3f000000u); }
__device__ __forceinline__ void delta(uint32_t* v, uint32_t key, uint32_t pos, const uint4* __restrict__ x, int c) {
  const int tap = (key >> 16) & 15, ki = (tap * 11) >> 5, gy = (int)bf16lo(pos), gx = (int)bf16hi(pos);
  const int cy = min(max((int)(key & 255) + ki - 1, 0), IH - 1), cx = min(max((int)((key >> 8) & 255) + tap - ki * 3 - 1, 0), IW - 1);
  const uint32_t sx = gx < IW - 1 ? 12 : 0, sy = gy < IH - 1 ? IW * 12 : 0, p = (gy * IW + gx) * 12 + c;
  uint4 t[5] = {__ldg(x + p), __ldg(x + (p + sx)), __ldg(x + (p + sy)), __ldg(x + (p + sy + sx)), __ldg(x + (uint32_t)((cy * IW + cx) * 12 + c))};
  uint32_t q0, q1;
  coefs(frac2(pos), q0, q1);
  blend4(&t[0].x, &t[1].x, &t[2].x, &t[3].x, q0, q1, q0, q1);
#pragma unroll
  for (int i = 0; i < 4; i++) v[i] = hsub2((&t[0].x)[i], (&t[4].x)[i]);
}
__device__ __forceinline__ void fixup(uint32_t bars, int w, int n, const uint4* __restrict__ x, const uint4* __restrict__ wgt) {
  const uint32_t fix = bars + SM_FIX - SM_BAR, part = fix + NREC * 192;
  const int lane = lane_now(), l = min(lane, 23), up = l >= 12;
#pragma unroll 1
  for (int r = 0; r < n; r++) {
    uint32_t key, pos, sum[4];
    lds64(key, pos, bars + O_REC + r * 8);
    key = __shfl_sync(0xffffffffu, key, 0);
    pos = __shfl_sync(0xffffffffu, pos, 0);
    delta(sum, key, pos, x, w * 3 + (l >> 3));
    sts128(part + w * 192 + (l >> 3) * 16, sum);
    __syncwarp();
#pragma unroll
    for (int i = 0; i < 4; i++) sum[i] = 0;
    const uint4* wp = wgt + (((key >> 16) & 15) * 96 + w * 24 + up * 11) * 12 + l;
#pragma unroll 1
    for (int h = 0; h < 3; h++) {
      uint4 wv[4];
      uint32_t d[2];
#pragma unroll
      for (int k = 0; k < 4; k++) wv[k] = __ldg(wp + (h * 4 + k) * 12);
      lds64(d[0], d[1], part + w * 192 + up * 24 + h * 8);
#pragma unroll
      for (int i = 0; i < 4; i++)
        sum[i] = hadd2(sum[i], hfma2_h(d[1], 1, (&wv[3].x)[i], hfma2_h(d[1], 0, (&wv[2].x)[i], hfma2_h(d[0], 1, (&wv[1].x)[i], hmul2_h(d[0], 0, (&wv[0].x)[i])))));
    }
#pragma unroll
    for (int i = 0; i < 4; i++) sum[i] = hadd2(sum[i], __shfl_down_sync(0xffffffffu, sum[i], 12));
    if (lane < 12) sts128(part + w * 192 + lane * 16, sum);
    bar_sync(4, 128);
    if (lane < 12) {
      float lo = 0.0f, hi = 0.0f;
#pragma unroll
      for (int k = 0; k < 4; k++) {
        const uint32_t v = lds32(part + k * 192 + w * 48 + lane * 4);
        lo += bf16lo(v);
        hi += bf16hi(v);
      }
      sts32(fix + r * 192 + w * 48 + lane * 4, pack2(lo, hi));
    }
    bar_sync(4, 128);
  }
}
__device__ __forceinline__ void patch(uint32_t bars, uint32_t mask, uint32_t key, uint32_t stg, uint32_t group, int lane) {
#pragma unroll 1
  for (; mask; mask &= mask - 1) {
    const uint32_t r = __ffs(mask) - 1, m = (__shfl_sync(0xffffffffu, key, r) >> 20) & 127;
    if (lane < 24) {
      const uint32_t a = stg + (lane >> 3) * group + m * 64 + ((((lane ^ m) >> 1) & 3) << 4) + (lane & 1) * 8;
      uint32_t v[2], c[2];
      lds64(v[0], v[1], a);
      lds64(c[0], c[1], bars + SM_FIX - SM_BAR + r * 192 + lane * 8);
      v[0] = hadd2(v[0], c[0]);
      v[1] = hadd2(v[1], c[1]);
      sts64(a, v);
    }
    __syncwarp();
  }
  fence_async();
  __syncwarp();
}

struct Maps {
  CUtensorMap x[5];
  CUtensorMap w[2];
  CUtensorMap o[2];
  CUtensorMap out[4];
};

__global__ void __cluster_dims__(2, 1, 1) __launch_bounds__(NTHREADS, 1)
dcn_kernel(const __nv_bfloat16* __restrict__ x, const uint32_t* __restrict__ offs, const uint4* __restrict__ wgt, Scratch* scr,
           const uint32_t never, const __grid_constant__ Maps tm) {
  extern __shared__ __align__(1024) uint8_t smem[];
  const uint32_t sbase = smem_u32(smem);
  const uint32_t bars = sbase + SM_BAR;
  const int tid = threadIdx.x;
  const int cta = blockIdx.x;
  const uint32_t tstart = clock32();
  const int wid = __shfl_sync(0xffffffffu, tid >> 5, 0);
  const int lane = tid & 31;
  const bool wino = cta < NW, strip = !wino && cta < NW + NG;
  const int left = cta >= NW + NG / 2;
  const int ry = (cta * 43) >> 9;
  const int x0 = wino ? 32 + (cta - ry * 12) * 16 : 32 + (cta - NW - left * (NG / 2)) * 8, y0 = 32 + ry * 32;
  auto load_cols = [&](int s, int j) {
    const uint32_t dst = sbase + (s ? SM_R : 4 * VSLOT) + j * 2 * PIECE, bar = bars + (B_XF + s * 5 + j) * 8;
    if (j < 4) tma_load_x4(dst, &tm.x[4], bar, s * 32, y0 - 1, (x0 >> 1) - 1 + j * 2);
    else tma_load_x(dst, &tm.x[0], bar, 0, s * 32, x0 + 15, y0 - 1);
  };
  auto corner_tile = [&](int wg) {
    const uint32_t t = ((wg ? 0xfbea00000000ull : 0xdc7398265410ull) >> (4 * (cta - NW - NG))) & 15;
    return (t & 3) | ((t >> 2) << 8);
  };
  const bool one = elect_one();
  if (wid == 15) {
    if (one) {
      if (wino) {
        asm volatile("prefetch.tensormap [%0];\n" ::"l"(reinterpret_cast<uint64_t>(&tm.x[4])) : "memory");
        asm volatile("prefetch.tensormap [%0];\n" ::"l"(reinterpret_cast<uint64_t>(&tm.x[0])) : "memory");
        mbar_init(bars + B_W2 * 8, 1);
#pragma unroll
        for (int k = 0; k < 9; k++)
          asm volatile("cp.async.bulk.shared::cluster.global.mbarrier::complete_tx::bytes [%0], [%1], 6144, [%2];\n" ::"r"(sbase + k * 6144 + (k < 6 ? 0 : 6 * VSLOT)),
                       "l"(wgt + k * 1152), "r"(bars + B_W2 * 8) : "memory");
        TS(6, 26);
      }
#pragma unroll
      for (int j = 0; j < 8; j++) mbar_init(bars + j * 8, 1);
      if (wino) {
#pragma unroll
        for (int j = 0; j < NA0; j++) load_cols(0, j);
        mbar_expect_tx(bars + B_W2 * 8, 9 * 6144);
      } else {
        mbar_expect_tx(bars + B_OG * 8, strip ? 4 * 2304 : 2 * 2304);
#pragma unroll
        for (int k = 0; k < 4; k++) {
          const uint32_t tl = corner_tile(k & 1);
          if (strip || k < 2)
            tma_load_o(sbase + (strip ? SM_GO + k * 2304 : SM_CX + k * CWIN + 2 * CSLICE), &tm.o[1], bars + B_OG * 8,
                       strip ? (left ? k * 8 : x0) : (tl & 255) * 8, strip ? (left ? x0 : k * 8) : (tl >> 8) * 8);
        }
        asm volatile("prefetch.tensormap [%0];\n" ::"l"(reinterpret_cast<uint64_t>(&tm.x[strip ? 1 + left : 3])) : "memory");
        asm volatile("prefetch.tensormap [%0];\n" ::"l"(reinterpret_cast<uint64_t>(&tm.w[left])) : "memory");
      }
      asm volatile("fence.mbarrier_init.release.cluster;\n" ::: "memory");
    }
    __syncwarp();
    TS(6, 25);
  }
  if (wid >= 4) {
    if (one && wid < 15) {
      const int grp = 15 - wid;
#pragma unroll
      for (int i = 0; i < 8; i++) mbar_init(bars + grp * 64 + i * 8, grp < 5 ? 1 : grp < 7 ? 16 : grp < 8 ? 8 : 4);
      asm volatile("fence.mbarrier_init.release.cluster;\n" ::: "memory");
    }
    __syncwarp();
  } else if (one) {
    if (wid == 3) {
      const uint32_t z[4] = {0, 0, 0, 0};
      sts64(bars + O_CNT, z);
      __threadfence_block();
    }
  }
  if (wid == 15) TS(6, 22);
  asm volatile("barrier.cluster.arrive.relaxed.aligned;\n" ::: "memory");
  const bool prep = wid >= 8 && wid < 11 && !wino && cta < NW + 24;
  uint4 g[3];
  if (prep) {
    const uint4* src = wgt + (uint32_t)((cta - NW + ((cta - NW) >> 3) * 4) * 96 + 352 + (tid >> 5) * 4 + (lane >> 2) * 12 + (lane & 3));
#pragma unroll
    for (int k = 0; k < 3; k++) g[k] = __ldg(src + k * 3456);
  }
  auto load_cw = [&](int st) {
    const uint32_t rank = cta & 1;
    const int g = (st * 11) >> 5;
    const uint32_t fb = bars + (B_WF + st) * 8;
    mbar_expect_tx(fb, STAGE);
    tma_load_w(sbase + st * STAGE, &tm.w[1], fb, g * 32, 0, st - g * 3, 1u << rank);
    tma_load_w(sbase + st * STAGE + STAGE / 2, &tm.w[1], fb, g * 32 + 16, 0, st - g * 3, 1u << rank);
  };
  auto load_cx = [&](int wg, int g, uint32_t tl) {
    tma_load_x(sbase + SM_CX + wg * CWIN + g * CSLICE, &tm.x[3], bars + (B_XF + wg * 3 + g) * 8, CSLICE, g * 32, (int)(tl & 255) * 8 - 2,
               (int)(tl >> 8) * 8 - 2);
  };
  asm volatile("barrier.cluster.wait.acquire.aligned;\n" ::: "memory");
  const uint8_t* udst = nullptr;
  if (wino ? wid < 12 : prep) {
    const int lane = lane_now();
    const uint32_t sw = (lane >> 2) * 64 + (((lane ^ (lane >> 3)) & 3) << 4);
    const uint32_t dst = sbase + (wid & 2) * (STAGE / 4) + (wid >> 2) * 1024 + (wid & 1) * 512 + sw;
    const uint32_t src = sbase + (wid & 3) * 1536 + (wid >> 2) * 64 + (lane >> 2) * 192 + (lane & 3) * 16;
    if (wino) mbar_wait(bars + B_W2 * 8);
    if (wid == 8) TS(7, 1);
#pragma unroll 1
    for (int kj = 0; kj < 3; kj++) {
      if (wino) {
        lds128(&g[0].x, src + kj * 6144);
        lds128(&g[2].x, src + kj * 6144 + 10 * VSLOT);
        lds128(&g[1].x, src + kj * 6144 + 18432);
      }
      uint32_t u[4][4];
      weights4(&g[0].x, &g[1].x, &g[2].x, u);
      if (!wino) {
        udst = scr->u + ((cta >> 2) & 1) * (4 * STAGE) + (cta & 2) * (STAGE / 4) + ((cta - NW) >> 3) * 3072 + (wid - 8) * 1024 + (cta & 1) * 512 + sw;
#pragma unroll
        for (int k = 0; k < 4; k++)
          asm volatile("st.relaxed.gpu.global.v4.b32 [%0], {%1, %2, %3, %4};\n" ::"l"(udst + k * STAGE), "r"(u[k][0]), "r"(u[k][1]), "r"(u[k][2]), "r"(u[k][3]) : "memory");
        break;
      }
#pragma unroll
      for (int k = 0; k < 4; k++) sts128(dst + kj * 3072 + w_slot(k), u[k]);
    }
    if (wino) {
      fence_async();
      bar_sync(12, 384);
    }
    if (wid == 8) TS(7, 0);
    if (wid < 8) {
      const int wg = wid >> 2;
      TSS(wg, 23);
      {
        const int q = wid + wg, tp = lane >> 3, h = tp * 18 + q;
        const uint32_t src = (sbase + 4 * VSLOT + q * PIECE + tp * 1024 + (lane & 7) * 16) & (x0 + 2 * q == IW ? ~64u : ~0u);
        const uint32_t vb = sbase + h * 128 + (lane & 4) * 16;
        mbar_wait(bars + (B_XF + (q >> 1)) * 8);
        uint32_t d[10][4];
#pragma unroll
        for (int r = 0; r < 9; r++) lds128(d[r], src + r * 128);
        lds128(d[9], src + (y0 + 32 == IH && tp == 3 ? 8 * 128 : 9 * 128));
        transform6<4>(d, vb + (((lane ^ h) & 3) << 4), 10 * VSLOT);
        transform6<4>(d + 4, vb + VROW + (((lane ^ (h + 1)) & 3) << 4), 10 * VSLOT);
        publish(bars + (wg ? B_VF + 1 : B_V0) * 8, lane);
      }
    }
  }
  if (wid < 8) {
    const int wg = wid >> 2, warp = wid & 3, lane = lane_now();
    if ((sbase & 0xffffff) != SB) __trap();
    TSS(wg, 25);
    asm volatile("setmaxnreg.inc.sync.aligned.u32 224;\n");
    TSS(wg, 26);
    uint32_t we_addr;
    asm volatile("mapa.shared::cluster.u32 %0, %1, %2;\n" : "=r"(we_addr) : "r"(bars + B_WE * 8), "r"(lane & 1));
    const uint32_t nv = never & (uint32_t)tid;
    float acc[4][48];
    int ntiles = 0;

    uint32_t tile0 = 0, tstep = 0;
    if (wino) {
      TSS(wg, 24);
      constexpr uint64_t bd0 = w_desc(SB);
      const uint64_t ad0 = a_desc(SB) + wg * 32;
      uint32_t rel = 0;
      if (lane == 3) we_addr = bars + (B_VE - 3) * 8;
      if (lane == 2) we_addr = bars + (B_WL - 13) * 8;
      uint32_t guard = never, gnext = never;
#define PIN_NEXT do { guard = gnext; gnext = clock32() & never; } while (0)
      auto stage = [&](float* a, int st, uint32_t rs, int vslot, uint32_t accumulate, auto work) {
        const uint64_t bd = bd0 + (rs >> 4), ad = ad0 + vslot * (VSLOT >> 4);
        mbar_wait(bars + (B_WF + st) * 8);
        TSS(wg, st);
        wgmma_fence();
#pragma unroll
        for (int j = 0; j < 6; j++) {
          wgmma_ss(a, ad + (j >> 1) * 4 + (j & 1) * 2, bd + (j >> 1) * WTAP + (j & 1) * WHALF, j ? 1 : accumulate);
          if (j == 1) {
            wgmma_commit();
            wgmma_wait<1>();
            arrive_if(rel);
            rel = ((lane < 2 ? 0xff7u : lane == 3 ? 8u : lane == 2 ? 0x2000u : 0u) >> st) & 1 ? we_addr + st * 8 : 0u;
          }
          if (j == 5) wgmma_commit();
          work(j);
        }
      };
#pragma unroll
      for (int p = 0; p < 4; p++) {
        wgmma_fence();
        wgmma_def(acc[p], w_desc(SB + SM_WW));
      }
      wgmma_commit();
      mbar_wait(bars + B_V0 * 8);
      if (wg) mbar_wait(bars + (B_VF + 1) * 8);
#pragma unroll 1
      for (int s = 0; s < 3; s++) {
        if (s) {
          const uint32_t vf = bars + (B_VF + 2 * s + wg) * 8;
          if (!mbar_test(vf) || (wg && s == 2)) {
            wgmma_wait<0>();
            arrive_if(rel);
            rel = 0;
            mbar_wait(vf);
            if (wg && s == 2) mbar_wait(bars + B_PP * 8);
          }
        }
#pragma unroll
        for (int p = 0; p < 4; p++) {
          stage(acc[p], s * 4 + p, (((uint32_t)w_slots(p, 4, 3) >> (8 * s)) & 255) << 10, (s & 1) * 4 + p, s, [&](int j) {
            if (p == 3 && j == PPJ) arrive_if(tid == 0 && s == 2 ? bars + B_PP * 8 : 0u);
          });
        }
      }
#pragma unroll
      for (int i = 0; i < 48; i++) {
        if (i % CHUNK == 0) PIN_NEXT;
        UPD_ADD(acc[0][i], acc[1][i], 1.0f);
        UPD_MUL(acc[1][i], acc[0][i], -2.0f);
      }
      wgmma_wait<0>();
      arrive_if(rel);
      rel = 0;
      TSS(wg, 18);
#pragma unroll
      for (int i = 0; i < 48; i++) {
        if (i % CHUNK == 0) PIN_NEXT;
        UPD_ADD(acc[2][i], acc[3][i], 1.0f);
        UPD_MUL(acc[3][i], acc[2][i], -2.0f);
        UPD_ADD(acc[2][i], acc[0][i], 0.5f);
        UPD_ADD(acc[1][i], acc[3][i], 0.5f);
        UPD_ADD(acc[0][i], acc[2][i], 2.0f / 15.0f);
        UPD_ADD(acc[3][i], acc[1][i], 2.0f / 15.0f);
      }
      TSS(wg, 19);
      const uint32_t stg = sbase + warp * 1024, stb = bars + (B_ST + wg * 4) * 8;
      mbar_wait(bars + (wg ? B_WE + 9 : B_SW) * 8);
      stage_slab<4096, true>(acc[2], stg + guard + gnext + w_stg(wg, 2), lane);
      stage_slab<4096, true>(acc[1], stg + w_stg(wg, 1), lane);
#pragma unroll 1
      for (int k = 0; k < 3; k++) {
        stage(acc[0], 12 + k, (((uint32_t)w_slots(12, 1, 3) >> (8 * k)) & 255) << 10, (0xc8a >> (4 * k)) & 15, 1, [&](int j) {
          if (j == 2 && k == 0) {
            fence_async();
            __syncwarp();
            arrive_if(lane < 2 ? stb + 8 + lane * 8 : 0u);
          }
        });
      }
#pragma unroll 1
      for (int k = 0; k < 3; k++) {
        stage(acc[3], 15 + k, (((uint32_t)w_slots(15, 1, 3) >> (8 * k)) & 255) << 10, (0xd9b >> (4 * k)) & 15, 1, [&](int j) {
          if (j == O1J && k == (wg ? 0 : O0K)) {
            mbar_wait(bars + (wg ? B_WL : B_SR) * 8);
            acc_fence(acc[0]);
            stage_slab(acc[0], stg + w_stg(wg, 0), lane);
          }
          if (j == 1 && k == (wg ? 1 : O0K + 1)) publish(stb, lane);
        });
      }
      wgmma_wait<0>();
      acc_fence(acc[3]);
      TSS(wg, 20);
      stage_slab(acc[3], stg + w_stg(wg, 3), lane);
      publish(stb + 24, lane);
      TSS(wg, 21);
      mbar_wait(bars + B_SW * 8);
      mbar_wait(bars + B_IM * 8);
      if (lds32(bars + O_CNT) + lds32(bars + O_CNT + 4) > NREC) {
        ntiles = 4;
        tile0 = (x0 >> 3) + wg + (y0 << 5);
        tstep = 0x100;
      }
    } else if (strip) {
      const uint32_t tab = sbase + SM_GT + wid * 1152;
      TSS(wg, 28);
      {
        const int r = (warp & 1) * 4 + (lane & 3), c = lane >> 2, pu = wid * 4 + (lane & 3), pv = x0 + c;
        const uint32_t oa = sbase + SM_GO + (wid >> 1) * 2304 + (left ? c * 8 + r : r * 8 + c) * 36, swap = left ? 0x3210u : 0x1032u;
        uint32_t bad = 0;
        mbar_wait(bars + B_OG * 8);
        TSS(wg, 29);
#pragma unroll 1
        for (int tv = 0; tv < 3; tv++) {
          const uint32_t base = pack2((float)(pv + tv - 1), (float)pu);
#pragma unroll
          for (int tu = 0; tu < 3; tu++) {
            const int tap = left ? tv * 3 + tu : tu * 3 + tv;
            const uint32_t gp = hadd2(base, tap_delta(1, tu));
            uint32_t d = hsub2(clip2(hadd2(gp, prmt(lds32(oa + tap * 4), 0, swap))), clip2(gp));
            const bool out = tu == 0 && pu == 0, off = strip_off(d, out);
            bad |= off ? 1u << tap : 0u;
            d = out ? 0x3f800000u : off ? 0u : d & 0xffff0000u;
            sts32(tab + tv * 384 + tu * 128 + lane * 4, d | ((int)d < 0 ? 0x7654u : 0x3210u));
          }
        }
        if (bad && pv >= 34) push_taps(bars, strip_key(pu, pv, left), bad, offs);
        __syncwarp();
        arrive_if(lane == 0 ? bars + B_SG * 8 : 0u);
      }
#pragma unroll
      for (int i = 0; i < 48; i++) acc[0][i] = acc[1][i] = 0.0f;
      uint32_t la[3];
#pragma unroll
      for (int tv = 0; tv < 3; tv++) {
        const int p = (warp * 4 + ((lane >> 3) & 1)) * 10 + min((lane & 7) + tv, IW - x0);
        la[tv] = sbase + wg * GWIN + p * 64 + ((((lane >> 4) ^ (p >> 1)) & 3) << 4);
      }
      uint32_t D[2][8][2], A[3][8], dl[3][4];
#pragma unroll
      for (int i = 0; i < 24; i++) A[0][i] = nv;
#pragma unroll
      for (int tu = 0; tu < 3; tu++) lds128(dl[tu], tab + tu * 128 + (lane >> 2) * 16);
      auto fetch = [&](int b, uint32_t a) {
#pragma unroll
        for (int i = 0; i < 4; i++) ldsm4(D[b][2 * i][0], D[b][2 * i + 1][0], D[b][2 * i][1], D[b][2 * i + 1][1], (a ^ (((i + b) & 1) * 32)) + i * 2 * GROW);
      };
      TSS(wg, 23);
      mbar_wait(bars + (B_XF + wg * 3) * 8);
      fetch(0, la[0]);
      TSS(wg, 24);
      int tn = 1;
#pragma unroll 1
      for (int st = 0; st < 9; st++) {
        const uint64_t bd = w_desc(SB + SM_GW) + (st < 7 ? st : st - 7) * (STAGE >> 4);
        mbar_wait(bars + (B_XF + wg * 3 + (st >= 5 ? 2 : st >= 2)) * 8);
        mbar_wait(bars + (B_WF + st) * 8);
        TSS(wg, st);
#pragma unroll
        for (int kh = 0; kh < 2; kh++) {
          fetch(kh ^ 1, la[kh]);
          uint32_t E[7][2];
#pragma unroll
          for (int tu = 0; tu < 3; tu++) {
            wgmma_wait<2>();
            keep_alive8(A[tu], nv);
            if (kh == 1 && tu == 0) arrive_if((st == 1 || st == 2) && lane < 2 ? we_addr + st * 8 - 8 : 0u);
#pragma unroll
            for (int i = 0; i < 8; i++) {
              const int r = (i >> 2) * 2 + (i & 1), h = (i >> 1) & 1;
              if (tu == 0 && r == 0) E[0][h] = hsub2(D[kh][1][h], D[kh][0][h]);
              if (tu == 0 || r == 3) E[r + tu + 1][h] = hsub2(D[kh][r + tu + 2][h], D[kh][r + tu + 1][h]);
              A[tu][i] = hfma2_h(dl[tu][r], 1, prmt(E[r + tu + 1][h], E[r + tu][h], dl[tu][r]), D[kh][r + tu + 1][h]);
              if ((i & 3) == 3) {
                wgmma_fence();
                wgmma_rs(acc[i >> 2], A[tu] + (i & 4), bd + tu * WTAP + kh * WHALF);
              }
            }
            wgmma_commit();
            if (kh) lds128(dl[tu], tab + tn * 384 + tu * 128 + (lane >> 2) * 16);
          }
        }
        const uint32_t l0 = la[0] + (st < 6 ? GSLICE : 0);
        la[0] = la[1];
        la[1] = la[2];
        la[2] = l0;
        tn = tn == 2 ? 0 : tn + 1;
      }
      wgmma_wait<0>();
#pragma unroll
      for (int i = 0; i < 3; i++) keep_alive8(A[i], nv);
      acc_fence(acc[0]);
      acc_fence(acc[1]);
      TSS(wg, 20);
      bar_sync(1 + wg, 128);
      const uint32_t stg = sbase + wg * GWIN + warp * 2048;
      stage_slab<8192>(acc[0], stg, lane);
      stage_slab<8192>(acc[1], stg + 1024, lane);
      publish(bars + (B_ST + wg * 4) * 8, lane);
      TSS(wg, 21);
      mbar_wait(bars + B_SG * 8);
      mbar_wait(bars + B_IM * 8);
      if (lds32(bars + O_CNT) + lds32(bars + O_CNT + 4) > NREC) {
        ntiles = 2;
        tile0 = left ? wg * 2 + (x0 << 5) : (x0 >> 3) + (wg << 9);
        tstep = left ? 1 : 0x100;
      }
    } else {
      ntiles = !wg || cta >= GRID - 4;
      tile0 = corner_tile(wg);
      if (!ntiles) {
        const int src = cta - NW - NG, t = tid & 127;
        arrive_if(lane == 0 ? bars + B_SG * 8 : 0u);
        const uint32_t tag = scr->launch[cta] + 1;
        const int lf = src < 7 ? src >= 4 : t < 64;
        const int along = src < 4 ? 32 + src * 48 + (t >> 1) : src < 7 ? src * 64 - 224 + (t >> 1) : (t >> 1) & 31;
        const int oy = lf ? along : 32 + (t & 1), ox = lf ? 32 + (t & 1) : along;
        if (src < 4 ? t < 96 : src == 7 || along >= 34) {
          const uint32_t key = src < 7 ? wino_key(oy, ox) : strip_key(along, 32 + (t & 1), !lf);
          uint32_t o2[9];
          TSS(wg, 3);
#pragma unroll
          for (int m = 0; m < 9; m++) o2[m] = __ldg(offs + (oy * IW + ox) * 9 + m);
          TSS(wg, 4);
#pragma unroll 1
          for (int m = 0; m < 9; m++) {
            const int ki = (m * 11) >> 5, gy = oy + ki - 1, gx = ox + m - ki * 3 - 1;
            const uint32_t gp = pack2((float)gy, (float)gx), pos = clip2(hadd2(gp, o2[0])), d = hsub2(pos, clip2(gp));
            if (strip_off(lf ? prmt(d, 0, 0x1032) : d, src < 7 || (gy | gx) < 0)) push_record(bars, key | (m << 16), pos);
#pragma unroll
            for (int k = 0; k < 8; k++) o2[k] = o2[k + 1];
          }
        }
        bar_sync(2, 128);
        TSS(wg, 0);
        const int n = __shfl_sync(0xffffffffu, lds32(bars + O_CNT), 0);
        if (n && n <= NREC) {
          const uint32_t tmp = sbase + SM_CX + CWIN;
#pragma unroll 1
          for (int i = t; i < n * 12; i += 128) {
            const int r = (i * 171) >> 11;
            uint32_t key, pos, v[4];
            lds64(key, pos, bars + O_REC + r * 8);
            delta(v, key, pos, reinterpret_cast<const uint4*>(x), i - r * 12);
            sts128(tmp + (r + i) * 16, v);
          }
          bar_sync(2, 128);
          TSS(wg, 5);
          const int r0 = warp ? 99 : lane >> 2;
          const uint32_t k0 = lds32(bars + O_REC + (lane >> 2) * 8), k1 = lds32(bars + O_REC + 64 + (lane >> 2) * 8);
          const uint32_t t0 = r0 < n ? (k0 >> 16) & 15 : 15, t1 = r0 + 8 < n ? (k1 >> 16) & 15 : 15;
          const uint32_t taps = __reduce_or_sync(0xffffffffu, lane < n ? 1u << ((lds32(bars + O_REC + (lane & 15) * 8) >> 16) & 15) : 0u);
          uint32_t D[6][4];
#pragma unroll
          for (int k = 0; k < 6; k++) ldsm4(D[k], tmp + (lane & 15) * 208 + (lane >> 4) * 16 + k * 32);
#pragma unroll
          for (int i = 0; i < 48; i++) acc[0][i] = 0.0f;
#pragma unroll 1
          for (uint32_t m = taps; m; m &= m - 1) {
            const uint32_t tap = __ffs(m) - 1, ki = (tap * 11) >> 5;
            uint32_t A[6][4];
#pragma unroll
            for (int k = 0; k < 6; k++) {
#pragma unroll
              for (int i = 0; i < 4; i++) A[k][i] = (i & 1 ? t1 : t0) == tap ? D[k][i] : 0u;
            }
#pragma unroll
            for (int g = 0; g < 3; g++) mbar_wait(bars + (B_WF + g * 3 + ki) * 8);
            wgmma_fence();
#pragma unroll
            for (int k = 0; k < 6; k++)
              wgmma_rs(acc[0], A[k], w_desc(SB) + ((k >> 1) * 3 + ki) * (STAGE >> 4) + (tap - ki * 3) * WTAP + (k & 1) * WHALF);
            wgmma_commit();
            wgmma_wait<0>();
#pragma unroll
            for (int k = 0; k < 3; k++) keep_alive8(A[2 * k], nv);
          }
          acc_fence(acc[0]);
          TSS(wg, 6);
          uint32_t* dst = reinterpret_cast<uint32_t*>(scr->fix) + (src * NREC + (lane >> 2)) * 48 + (lane & 3);
          if (!warp) {
#pragma unroll
            for (int j = 0; j < 24; j++) dst[(j >> 1) * 4 + (j & 1) * 384] = pack2(acc[0][j * 2], acc[0][j * 2 + 1]);
          }
        }
        TSS(wg, 1);
        if (!warp) {
          __threadfence();
          __syncwarp();
          if (lane < NREC)
            asm volatile("st.relaxed.gpu.global.v2.u32 [%0], {%1, %2};\n" ::"l"(scr->key + src * NREC + lane), "r"(lds32(bars + O_REC + lane * 8)),
                         "r"((tag << 8) | min(n, 99)) : "memory");
          if (lane == 0) scr->launch[cta] = tag;
        }
        TSS(wg, 2);
      }
    }
    if (ntiles) {
      const uint32_t winb = sbase + SM_CX + wg * CWIN, tab = sbase + SM_CT + wid * 1152;
      const uint32_t ck = (uint32_t)(lane >> 4) << 4, again = tstep != 0;
      if (tstep) {
        bar_sync(3, 256);
        if (wid == 0 && one) {
#pragma unroll 1
          for (int st = 0; st < 9; st++) load_cw(st);
        }
        __syncwarp();
      }
#pragma unroll 1
      for (int n = 0; n < ntiles; n++) {
        const uint32_t tl = tile0 + n * tstep;
        const int wx0 = (int)(tl & 255) * 8 - 2, wy0 = (int)(tl >> 8) * 8 - 2;
        if (tstep && warp == 0 && one) {
#pragma unroll 1
          for (int g = 0; g < 3; g++) load_cx(wg, g, tl);
        }
        __syncwarp();
        TSS(wg, 28);
        uint32_t mout = 0, need = 0, of[5];
        {
          const int ph = wy0 + 2 + 2 * warp + ((lane >> 3) & 1), pw = wx0 + 2 + (lane & 7);
          if (tstep) {
#pragma unroll
            for (int k = 0; k < 5; k++) of[k] = __ldg(offs + (ph * IW + pw) * 9 + min((lane >> 4) + 2 * k, 8));
          } else {
            mbar_wait(bars + B_OG * 8);
#pragma unroll
            for (int k = 0; k < 5; k++) of[k] = lds32(winb + 2 * CSLICE + (warp * 16 + (lane & 15)) * 36 + min((lane >> 4) + 2 * k, 8) * 4);
          }
#pragma unroll 1
          for (int m = lane >> 4; m < 9; m += 2) {
            const int ki = (m * 11) >> 5;
            const uint32_t pos = clip2(hadd2(pack2((float)(ph + ki - 1), (float)(pw + m - ki * 3 - 1)), of[0]));
#pragma unroll
            for (int k = 0; k < 4; k++) of[k] = of[k + 1];
            const uint32_t iy = (int)bf16lo(pos) - wy0, ix = (int)bf16hi(pos) - wx0, f = frac2(pos);
            mout |= max(iy, ix) > 10 ? 1u << m : 0u;
            need |= ((f >> 16 ? 1u : 0u) | (f & 0xffffu ? 0x200u : 0u) | (f >> 16 && f & 0xffffu ? 0x40000u : 0u)) << m;
            const uint32_t pp = (iy * 12 + ix) * 0x10001u + 0x10000u;
            sts32(tab + m * 64 + (lane & 7) * 8 + ((lane >> 1) & 4), f);
            sts32(tab + 576 + m * 64 + (lane & 15) * 4, pp * 64 + ((pp << 3) & 0x300030u));
            of[4] = pos;
          }
          mout = __reduce_or_sync(0xffffffffu, mout);
          need = __reduce_or_sync(0xffffffffu, need);
          arrive_if(lane == 0 && !tstep ? bars + B_SG * 8 : 0u);
        }
        TSS(wg, 29);
        uint32_t outside;
        asm volatile("{\n.reg .pred p, q;\nsetp.ne.u32 p, %1, 0;\nbarrier.red.or.pred q, %2, 128, p;\nselp.u32 %0, 1, 0, q;\n}\n"
                     : "=r"(outside) : "r"(mout), "r"(1 + wg) : "memory");
        outside = __shfl_sync(0xffffffffu, outside, 0);
#pragma unroll
        for (int i = 0; i < 48; i++) acc[0][i] = 0.0f;
        if (!outside) {
          uint32_t T[3][4], C[2][3][4];
#pragma unroll
          for (int i = 0; i < 12; i++) T[0][i] = C[0][0][i] = C[1][0][i] = nv;
          uint32_t ad[4];
          auto fetch = [&](int k, uint32_t e, uint32_t slice, uint32_t nd) {
            if (!(k & 1)) {
              ad[0] = (e & 0xffffu) + slice;
              ad[1] = (e >> 16) + slice;
              ad[2] = ad[0] ^ 32;
              ad[3] = ad[1] ^ 32;
            }
            ldsm4_if(T[k % 3], ad[(k & 1) * 2], never ^ 1);
            ldsm4_if(C[k & 1][0], ad[(k & 1) * 2 + 1], nd & 1);
            ldsm4_if(C[k & 1][1], ad[2 - (k & 1) * 2] + CROW, nd & 0x200u);
            ldsm4_if(C[k & 1][2], ad[3 - (k & 1) * 2] + CROW, nd & 0x40000u);
          };
          TSS(wg, 30);
          uint32_t ent[3], slice = winb;
          const uint32_t ck2 = ck * 0x10001u;
          mbar_wait(bars + (B_XF + wg * 3) * 8, (n + again) & 1);
          fetch(0, lds32(tab + 576 + (lane & 15) * 4) ^ ck2, slice, need);
          int ki = 0, g = 0;
#pragma unroll 1
          for (int st = 0; st < 9; st++) {
            const uint64_t bd = w_desc(SB) + st * (STAGE >> 4);
            const int kn = ki == 2 ? 0 : ki + 1;
            uint32_t cf[3][4];
#pragma unroll
            for (int j = 0; j < 3; j++) {
              uint32_t wA, wB;
              lds64(wA, wB, tab + (ki * 3 + j) * 64 + (lane >> 2) * 8);
              ent[j] = lds32(tab + 576 + (j < 2 ? ki * 3 + j + 1 : kn * 3) * 64 + (lane & 15) * 4) ^ ck2;
              coefs(wA, cf[j][0], cf[j][1]);
              coefs(wB, cf[j][2], cf[j][3]);
            }
            if (kn == 0 && g < 2) mbar_wait(bars + (B_XF + wg * 3 + g + 1) * 8, (n + again) & 1);
            mbar_wait(bars + (B_WF + st) * 8, again);
            TSS(wg, st);
#pragma unroll
            for (int k = 0; k < 6; k++) {
              wgmma_wait<1>();
              if (k == 5 && kn == 0 && g < 2) {
                g++;
                slice += CSLICE;
              }
              fetch(k + 1, ent[k >> 1], slice, need >> (k < 5 ? ki * 3 + ((k + 1) >> 1) : kn * 3));
              blend4(T[k % 3], C[k & 1][0], C[k & 1][1], C[k & 1][2], cf[k >> 1][0], cf[k >> 1][1], cf[k >> 1][2], cf[k >> 1][3]);
              wgmma_fence();
              wgmma_rs(acc[0], T[k % 3], bd + (k >> 1) * WTAP + (k & 1) * WHALF);
              wgmma_commit();
            }
            ki = kn;
          }
          wgmma_wait<0>();
          keep_alive8(T[0], nv);
          keep_alive8(T[1], nv);
        } else {
#pragma unroll
        for (int k = 0; k < 5; k++) {
          const int m = 2 * k - (lane >> 4);
          if (m >= 0) sts32(tab + m * 64 + (lane & 7) * 8 + ((lane >> 1) & 4), of[k]);
        }
        __syncwarp();
        uint32_t buf[2][8];
#pragma unroll
        for (int i = 0; i < 16; i++) buf[0][i] = nv;
        const uint32_t tmp = tab + 576 + lane * 16;
        int tap = 0, g = 0;
#pragma unroll 1
        for (int d = 0;; d += 2) {
#pragma unroll
          for (int b = 0; b < 2; b++) {
            const int k = d + b, q = (k * 11) >> 5;
            if (k == 27) goto tile_done;
            mbar_wait(bars + (B_XF + wg * 3 + g) * 8, (n + again) & 1);
            mbar_wait(bars + (B_WF + q) * 8, again);
            if (k == q * 3) TSS(wg, q);
            const uint32_t pos = lds32(tab + tap * 64 + (lane & 7) * 8 + ((lane >> 1) & 4));
            const int gy = (int)bf16lo(pos), gx = (int)bf16hi(pos);
            uint32_t T[8];
            if (!((mout >> tap) & 1)) {
              uint32_t wA, wB, pA0, pA1, pB0, pB1, G[4], H[4], K[4];
              lds64(wA, wB, tab + tap * 64 + (lane >> 2) * 8);
              const uint32_t slice = winb + g * CSLICE;
              const uint32_t p = (gy - wy0) * 12 + gx - wx0, p1 = p + 1;
              const uint32_t a00 = slice + p * 64 + (((p << 3) & 0x30) ^ ck), a01 = slice + p1 * 64 + (((p1 << 3) & 0x30) ^ ck);
              coefs(frac2(wA), pA0, pA1);
              coefs(frac2(wB), pB0, pB1);
#pragma unroll
              for (int hf = 0; hf < 2; hf++) {
                ldsm4(T + hf * 4, a00 ^ (hf * 32));
                ldsm4(G, a01 ^ (hf * 32));
                ldsm4(H, (a00 + CROW) ^ (hf * 32) ^ 32);
                ldsm4(K, (a01 + CROW) ^ (hf * 32) ^ 32);
                blend4(T + hf * 4, G, H, K, pA0, pA1, pB0, pB1);
              }
            } else {
              uint32_t q0, q1;
              coefs(frac2(pos), q0, q1);
              const int sx = gx < IW - 1 ? IC / 8 : 0, sy = gy < IH - 1 ? IW * IC / 8 : 0;
              const uint4* pc = reinterpret_cast<const uint4*>(x) + (gy * IW + gx) * (IC / 8) + g * 4 + (lane >> 4);
#pragma unroll
              for (int hf = 0; hf < 2; hf++) {
                uint4 v[4];
                v[0] = __ldg(pc + hf * 2);
                v[1] = __ldg(pc + hf * 2 + sx);
                v[2] = __ldg(pc + hf * 2 + sy);
                v[3] = __ldg(pc + hf * 2 + sy + sx);
                blend4(&v[0].x, &v[1].x, &v[2].x, &v[3].x, q0, q1, q0, q1);
                __syncwarp();
                sts128(tmp, &v[0].x);
                __syncwarp();
                ldsm4(T + hf * 4, tmp);
              }
            }
            wgmma_wait<1>();
            keep_alive8(buf[b], nv);
#pragma unroll
            for (int i = 0; i < 8; i++) asm volatile("xor.b32 %0, %1, %2;\n" : "=r"(buf[b][i]) : "r"(T[i]), "r"(nv));
            const uint64_t bd = w_desc(SB) + q * (STAGE >> 4) + (k - q * 3) * WTAP;
            wgmma_fence();
            wgmma_rs(acc[0], buf[b], bd);
            wgmma_rs(acc[0], buf[b] + 4, bd + WHALF);
            wgmma_commit();
            if (++tap == 9) {
              tap = 0;
              g++;
            }
          }
        }
      tile_done:
        wgmma_wait<0>();
        keep_alive8(buf[0], nv);
        keep_alive8(buf[1], nv);
        }
        acc_fence(acc[0]);
        TSS(wg, 20);
        bar_sync(1 + wg, 128);
        stage_slab(acc[0], winb + warp * 1024, lane);
        fence_async();
        bar_sync(1 + wg, 128);
        if (warp == 0 && one) {
          tma_store(&tm.out[3], winb, wx0 + 2, wy0 + 2, 0);
          asm volatile("cp.async.bulk.wait_group.read 0;\n" ::: "memory");
        }
        TSS(wg, 21);
      }
    }
    if (warp == 0) TSDUMP(wg);
  } else if (wid < 12) {
    asm volatile("setmaxnreg.dec.sync.aligned.u32 40;\n");
    if (prep) {
      uint32_t chk = 0;
#pragma unroll
      for (int k = 0; k < 4; k++) {
        uint32_t v;
        asm volatile("ld.relaxed.gpu.global.b32 %0, [%1];\n" : "=r"(v) : "l"(udst + k * STAGE) : "memory");
        chk |= v;
      }
      chk = __reduce_or_sync(0xffffffffu, chk & never);
      if (one) asm volatile("red.relaxed.gpu.global.add.u32 [%0], %1;\n" ::"l"(scr->cnt), "r"(chk + 1) : "memory");
      TS(5, 21);
    }
    const int w = wid - 8, lane = lane_now();
    if (wino) {
      arrive_if(one ? bars + (B_WF + w) * 8 : 0u);
      const int hi = w >> 1, ty = (w & 1) * 4 + (lane >> 4);
      const bool bottom = y0 + 4 * ty + 12 == IH;
      uint32_t d[2][6][2];
      auto fetch = [&](int u, uint32_t src, bool low = false) {
#pragma unroll
        for (int r = 0; r < 5; r++) lds64(d[u][r][0], d[u][r][1], src + u * 1024 + r * 128);
        lds64(d[u][5][0], d[u][5][1], src + u * 1024 + ((u || low) && bottom ? 4 * 128 : 5 * 128));
      };
      const uint32_t src = sbase + SM_R + hi * PIECE + ty * 512 + (lane & 15) * 8;
      uint32_t v0 = sbase + ty * VROW + hi * 128 + (lane & 8) * 8 + (lane & 1) * 8 + ((((lane >> 1) ^ (ty + hi)) & 3) << 4);
      const uint32_t vl = (v0 & ~0x30u) + 1024 + hi * (2 * VROW - 128) + ((((lane >> 1) ^ (ty + 2 * hi)) & 3) << 4);
      mbar_wait(bars + (B_XF + 2) * 8);
      fetch(0, src + 4 * VSLOT - SM_R + (4 - hi) * PIECE + hi * 1024, hi);
      transform6<2>(d[0], vl - 512, 10 * VSLOT);
      publish(bars + B_V0 * 8, !one);
      mbar_wait(bars + B_V0 * 8);
      mbar_wait(bars + (B_VF + 1) * 8);
      v0 += 4 * VSLOT;
#pragma unroll 1
      for (int s = 0; s < 2; s++) {
        const uint32_t xf = bars + (B_XF + 5 + s * 5) * 8, off0 = s ? 12 * VSLOT : 4 * VSLOT;
        if (s) mbar_wait(bars + B_VE * 8);
        mbar_wait(xf);
        fetch(0, src);
#pragma unroll 1
        for (int jj = 0; jj < 4; jj += 2) {
#pragma unroll
          for (int e = 0; e < 2; e++) {
            const int j = jj + e;
            if (w == 0) TS(7, 5 + s * 5 + j);
            const uint32_t ready = mbar_poll(xf + j * 8 + 8);
            fetch(1, src + j * 2 * PIECE);
            transform6<2>(d[0], (v0 ^ e * 32) + j * 256, off0);
            if (!ready) mbar_wait(xf + j * 8 + 8);
            fetch(0, (src + (j + 1) * 2 * PIECE - (j == 3 ? hi * (PIECE - 1024) : 0)) & (j == 3 && x0 + 16 == IW ? ~64u : ~0u), j == 3 && hi);
            transform6<2>(d[1], (v0 ^ (e ^ 1) * 32) + j * 256 + 2 * VROW, off0);
            __syncwarp();
            arrive_if(one && (!s || j == 2) ? bars + (B_RE + j + s * 3) * 8 : 0u);
            if (j + hi == 2) publish(bars + (B_VF + 2 + s * 2) * 8, !one);
          }
        }
        if (w == 0) TS(7, 9 + s * 5);
        transform6<2>(d[0], vl + (s ? 0 : 4 * VSLOT), off0);
        publish(bars + (B_VF + 3 + s * 2) * 8, !one);
        arrive_if(one && !s ? bars + (B_RE + 4) * 8 : 0u);
        v0 -= 4 * VSLOT;
      }
      if (w == 0) TS(7, 15);
        {
          mbar_wait(bars + B_OF * 8);
          if (w == 0) TS(7, 16);
          const uint32_t ob = sbase + SM_R + w * 4608;
          __nv_bfloat162 mx = as_bf2(0u);
#pragma unroll
          for (int h = 0; h < 2; h++) {
            uint32_t v[5][4];
#pragma unroll
            for (int k = 0; k < 5 - h; k++) lds128(v[k], ob + (h * 5 + k) * 512 + lane * 16);
#pragma unroll
            for (int k = 0; k < 5 - h; k++)
              mx = __hmax2_nan(mx, __hmax2_nan(__hmax2_nan(__habs2(as_bf2(v[k][0])), __habs2(as_bf2(v[k][1]))),
                                               __hmax2_nan(__habs2(as_bf2(v[k][2])), __habs2(as_bf2(v[k][3])))));
          }
          const uint32_t lim = (pack2((float)max(y0, 34) - 1.5f, (float)max(x0, 34) - 1.5f) & 0x7f807f80u) - 0x04000400u;
          uint32_t who = __ballot_sync(0xffffffffu, (as_u32(mx) & 0xffffu) >= (lim & 0xffffu) || (as_u32(mx) >> 16) >= (lim >> 16));
#pragma unroll 1
          for (; who; who &= who - 1) {
#pragma unroll 1
            for (int k = lane; k < 64; k += 32) {
              const int wd = (k >> 2) * 128 + (__ffs(who) - 1) * 4 + (k & 3), c = (wd * 7282) >> 16, tap = wd - c * 9, ki = (tap * 11) >> 5;
              const int y = y0 + w * 8 + (c >> 4), xx = x0 + (c & 15);
              if (k < 36 && min(y, xx) >= 34) {
                const uint32_t gp = pack2((float)(y + ki - 1), (float)(xx + tap - ki * 3 - 1));
                const uint32_t pos = clip2(hadd2(gp, lds32(ob + wd * 4)));
                if (pos != clip2(gp)) push_record(bars, wino_key(y, xx) | (tap << 16), pos);
              }
              __syncwarp();
            }
          }
          bar_sync(8 + w, 32);
          arrive_if(one ? bars + B_SW * 8 : 0u);
        }
      if (w == 0) TS(7, 17);
    }
    if (wino || strip) {
      mbar_wait(bars + (wino ? B_SW : B_SG) * 8);
      mbar_wait(bars + B_IM * 8);
      if (w == 0 && one) {
        atomicAdd(scr->launch + cta, 1);
        if (wino) atomicInc(scr->cnt, 72 + NW - 1);
      }
      uint32_t n0, n1;
      lds64(n0, n1, bars + O_CNT);
      n0 = __shfl_sync(0xffffffffu, n0 + n1 <= NREC ? n0 : 0, 0);
      if (n0) {
        fixup(bars, w, n0, reinterpret_cast<const uint4*>(x), wgt);
        asm volatile("bar.arrive 5, 192;\n" ::: "memory");
      }
      if (w == 0) TS(7, 21);
      if (w == 0) TSDUMP(7);
    }
  } else {
    if (wid == 15) TS(6, 23);
    asm volatile("setmaxnreg.dec.sync.aligned.u32 24;\n");
    if (wid >= 14 && !wino) {
      if (one) {
        const bool wt = wid == 15;
        const uint32_t t0 = wt ? (strip ? GW0 : CW0) : strip ? GX0 : CX0;
#pragma unroll 1
        for (int k = 0; k < (wt ? 9 : 6); k++) {
          const int g = wt ? (k * 11) >> 5 : k >> 1, r = wt ? k - g * 3 : k & 1;
          if (strip && k >= 7) mbar_wait(bars + (B_WE + k - 7) * 8);
          else wait_until(tstart, t0 + (wt ? k * (strip ? GWS : CWS) : strip ? g * GXS + r * (GX1 - GX0) : g * CXS));
          if (!wt && k == 4) mbar_wait(bars + B_SG * 8);
          if (wt) {
            const uint32_t fb = bars + (B_WF + k) * 8, hf = cta & 1, dst = sbase + (strip ? SM_GW + (k < 7 ? k : k - 7) * STAGE : k * STAGE);
            mbar_expect_tx(fb, STAGE);
            tma_load_w(dst + hf * (STAGE / 2), &tm.w[left], fb, g * 32 + hf * 16, left ? 0 : r, left ? r : 0, 3);
            TS1(6, k);
          } else if (strip || !r || cta >= GRID - 4) {
            const uint32_t tl = corner_tile(r);
            tma_load_x(sbase + (strip ? r * GWIN + g * GSLICE : SM_CX + r * CWIN + g * CSLICE), &tm.x[strip ? 1 + left : 3],
                       bars + (B_XF + r * 3 + g) * 8, strip ? GSLICE : CSLICE, g * 32, strip ? x0 - 1 : (int)(tl & 255) * 8 - 2,
                       strip ? r * 16 - 2 : (int)(tl >> 8) * 8 - 2);
          }
        }
      }
      __syncwarp();
    }
    if (wid == 15 && wino) {
      if (one) {
        if (NA0 < 5) wait_until(tstart, BDELAY);
#pragma unroll
        for (int j = NA0; j < 5; j++) load_cols(0, j);
        wait_until(tstart, SDELAY);
#pragma unroll
        for (int j = 0; j < NS1; j++) load_cols(1, j);
        wait_until(tstart, SDELAY + SDELAY2);
#pragma unroll
        for (int j = NS1; j < 5; j++) load_cols(1, j);
        TS(5, 0);
        wait_until(tstart, PDELAY);
        TS1(6, 20);
              asm volatile(
                  "{\n.reg .pred p;\n.reg .u32 n, v;\nmov.u32 n, 0;\n"
                  "W_%=:\n"
                  "ld.relaxed.gpu.global.u32 v, [%0];\nsetp.ge.u32 p, v, 72;\n"
                  "@p bra D_%=;\n"
                  "add.u32 n, n, 1;\nsetp.lt.u32 p, n, 0x100000;\n@p bra W_%=;\ntrap;\n"
                  "D_%=:\n}\n" ::"l"(scr->cnt)
                  : "memory");
              asm volatile("fence.proxy.async.global;\n" ::: "memory");
        TS1(6, 21);
      }
      bar_sync(13, 32);
    }
    if (wid == 15) TS(6, 24);
    if (wid == 15) {
      if (wino) {
#pragma unroll 1
        for (int k = 0; k < 8; k++) {
          mbar_wait(bars + (B_WE + ((0x77654210u >> (4 * k)) & 15)) * 8);
          if (one)
            bulk_load_mc(sbase + (uint32_t)((w_slots(4, 1, 8) >> (8 * k)) & 255) * 1024 + (cta & 1) * (STAGE / 2),
                         scr->u + (k * 2 + (cta & 1)) * (STAGE / 2), STAGE / 2, bars + (B_WF + 4 + k) * 8);
          TS1(6, 4 + k);
        }
#pragma unroll 1
        for (int k = 0; k < 6; k++) {
          mbar_wait(bars + (B_WE + min(7 + k, 11)) * 8);
          if (one)
            tma_load_w(sbase + (uint32_t)((w_slots(12, 1, 6) >> (8 * k)) & 255) * 1024 + (cta & 1) * (STAGE / 2), &tm.w[1],
                       bars + (B_WF + 12 + k) * 8, (k < 3 ? k : k - 3) * 32 + (cta & 1) * 16, 0, k < 3 ? 0 : 2, 3);
          TS1(6, 12 + k);
        }
      }
      TSDUMP(6);
    } else if (wid == 14) {
      if (one) {
        if (wino) {
#pragma unroll
          for (int j = 0; j < 5; j++) {
            mbar_wait(bars + (B_RE + j) * 8);
            load_cols(2, j);
            TS(5, 5 + j);
          }
        }
      }
      bar_sync(6, 32);
      if (wino || strip) {
        const int lane = lane_now();
        TS(5, 10);
        const uint32_t tag = scr->launch[cta] + 1;
        uint32_t n = 0;
#pragma unroll 1
        for (int k = wino && y0 == 32 ? 0 : 1; k < (x0 == 32 ? 2 : 1); k++) {
          const int src = !wino ? 7 : k ? 4 + (ry >> 1) : (cta * 11) >> 5;
          uint32_t key, v;
          asm volatile(
              "{\n.reg .pred p;\n.reg .u32 n, t;\nmov.u32 n, 0;\n"
              "W_%=:\n"
              "ld.acquire.gpu.global.v2.u32 {%0, %1}, [%2];\nxor.b32 t, %1, %3;\nsetp.lt.u32 p, t, 256;\nvote.sync.all.pred p, p, 0xffffffff;\n"
              "@p bra D_%=;\n"
              "add.u32 n, n, 1;\nsetp.lt.u32 p, n, 0x100000;\n@p bra W_%=;\ntrap;\n"
              "D_%=:\nfence.proxy.async.global;\n}\n"
              : "=r"(key), "=r"(v)
              : "l"(scr->key + src * NREC + (lane & 15)), "r"(tag << 8)
              : "memory");
          v &= 255;
          const uint32_t dy = (key & 255) - (wino ? y0 : left ? 32 : 0), dx = ((key >> 8) & 255) - (wino || !left ? x0 : 0);
          const bool mine = lane < v && dy < 32 && dx < (left ? 32 : 16);
          const uint32_t mask = __ballot_sync(0xffffffffu, mine), slot = NREC - 1 - n - __popc(mask & ((1u << lane) - 1));
          n = v > NREC ? 99 : n + __popc(mask);
          if (mine && n <= NREC) {
            sts32(bars + O_REC + 128 + slot * 4, key);
            asm volatile("mbarrier.expect_tx.relaxed.cta.shared::cta.b64 [%0], 192;\n" ::"r"(bars + B_IM * 8) : "memory");
            asm volatile("cp.async.bulk.shared::cluster.global.mbarrier::complete_tx::bytes [%0], [%1], 192, [%2];\n" ::"r"(sbase + SM_FIX + slot * 192),
                         "l"(scr->fix + (src * NREC + lane) * 12), "r"(bars + B_IM * 8) : "memory");
          }
          __syncwarp();
        }
        if (lane == 0) sts32(bars + O_CNT + 4, n + (tag & never));
        __syncwarp();
        arrive_if(lane == 0 ? bars + B_IM * 8 : 0u);
        TS(5, 11);
        TSDUMP(5);
      }
    } else if (wino || strip) {
      const int wg = wid - 12;
      if (one) {
        if (wino && wg) {
#pragma unroll 1
          for (int i = 4; i < 18; i++) mbar_expect_tx(bars + (B_WF + i) * 8, STAGE);
        } else if (wino) {
#pragma unroll 1
          for (int i = 0; i < 15; i++) mbar_expect_tx(bars + (B_XF + i) * 8, (0x4210 >> i) & 1 ? PIECE : 2 * PIECE);
        }
        asm volatile("prefetch.tensormap [%0];\n" ::"l"(reinterpret_cast<uint64_t>(&tm.out[wino ? 0 : 1 + left])) : "memory");
      }
      if (wino && !wg) {
        if (one) {
          wait_until(tstart, FDELAY);
          asm volatile("cp.async.bulk.prefetch.tensor.2d.L2.global [%0, {%1, %2}];\n" ::"l"(reinterpret_cast<uint64_t>(&tm.o[0])), "r"(x0 * 9), "r"(y0) : "memory");
          mbar_expect_tx(bars + B_OF * 8, 2 * VSLOT);
          mbar_wait(bars + B_R2 * 8);
          tma_load_o(sbase + SM_R, &tm.o[0], bars + B_OF * 8, x0, y0);
        }
        bar_sync(7, 32);
      }
      mbar_wait(bars + B_IM * 8);
      mbar_wait(bars + (wino ? B_SW : B_SG) * 8);
      uint32_t n0, n1;
      lds64(n0, n1, bars + O_CNT);
      const int lane = lane_now();
      if (__all_sync(0xffffffffu, n0 + n1 <= NREC)) {
        if (__any_sync(0xffffffffu, n0)) bar_sync(5, 192);
        uint32_t key = lds32(bars + O_REC + (lane < n0 ? lane * 8 : 128 + (lane & 15) * 4));
        if (!(lane < n0 || (lane < NREC && lane + n1 >= NREC))) key = ~0u;
        const uint32_t mine = __ballot_sync(0xffffffffu, key >> 29 == wg);
        const CUtensorMap* map = &tm.out[wino ? 0 : 1 + left];
        const int c1 = x0 + (wino ? wg * 8 : 0), c3 = wino ? y0 >> 2 : 0;
        TS1(wid - 10, 19);
#pragma unroll 1
        for (int i = wino ? 2 : 0;; i = (i - 1) & 3) {
          const uint32_t stg = sbase + (wino ? w_stg(wg, i) : wg * GWIN);
          mbar_wait(bars + (B_ST + wg * 4 + i) * 8);
          if (mine) patch(bars, __ballot_sync(0xffffffffu, key >> 27 == wg * 4 + i), key, stg, wino ? 4096 : 8192, lane);
          if (one) tma_store(map, stg, c1, wino ? i : wg * 16, c3);
          TS1(wid - 10, 20 + ((2 - i) & 3));
          if (i == 3 || !wino) break;
          if (i == 1 && !wg) {
            asm volatile("cp.async.bulk.wait_group.read 0;\n" ::: "memory");
            arrive_if(one ? bars + B_SR * 8 : 0u);
          }
        }
        asm volatile("cp.async.bulk.wait_group.read 0;\n" ::: "memory");
        TS1(wid - 10, 24);
      } else {
        arrive_if(one && !wg ? bars + B_SR * 8 : 0u);
      }
      TSDUMP(wid - 10);
    }
  }
}

typedef CUresult (*EncodeTiledFn)(CUtensorMap*, CUtensorMapDataType, cuuint32_t, void*, const cuuint64_t*,
                                  const cuuint64_t*, const cuuint32_t*, const cuuint32_t*, CUtensorMapInterleave,
                                  CUtensorMapSwizzle, CUtensorMapL2promotion, CUtensorMapFloatOOBfill);

}

extern "C" void kernel_launch(void* const* d_in, const int* in_sizes, int n_in, void* d_out, int out_size) {
  static EncodeTiledFn encode = nullptr;
  static void* scratch = nullptr;
  if (!encode) {
    cudaGetSymbolAddress(&scratch, g_scratch);
    void* fn = nullptr;
    cudaDriverEntryPointQueryResult qres;
    cudaGetDriverEntryPoint("cuTensorMapEncodeTiled", &fn, cudaEnableDefault, &qres);
    encode = (EncodeTiledFn)fn;
    cudaFuncSetAttribute(dcn_kernel, cudaFuncAttributeMaxDynamicSharedMemorySize, SMEM_BYTES);
  }
  Maps tm;
  const cuuint32_t es[5] = {1, 1, 1, 1, 1};
  constexpr cuuint64_t PX = IC * 2, ROW = IW * IC * 2;
  for (int i = 0; i < 4; i++) {
    const cuuint64_t dims[3] = {IC, IW, IH};
    const cuuint64_t strides[2] = {i == 2 ? ROW : PX, i == 2 ? PX : ROW};
    const cuuint32_t box[5][3] = {{32, 2, 34}, {32, 10, 20}, {32, 10, 20}, {32, 12, 12}, {32, 6, 34}};
    encode(&tm.x[i], CU_TENSOR_MAP_DATA_TYPE_BFLOAT16, 3, d_in[0], dims, strides, box[i], es, CU_TENSOR_MAP_INTERLEAVE_NONE,
           i & 3 ? CU_TENSOR_MAP_SWIZZLE_64B : CU_TENSOR_MAP_SWIZZLE_NONE, CU_TENSOR_MAP_L2_PROMOTION_NONE,
           CU_TENSOR_MAP_FLOAT_OOB_FILL_NONE);
  }
  {
    const cuuint64_t dims[4] = {IC, 2, IH, IW / 2 - 1};
    const cuuint64_t strides[3] = {PX, ROW, 2 * PX};
    const cuuint32_t box[4] = {32, 2, 34, 2};
    encode(&tm.x[4], CU_TENSOR_MAP_DATA_TYPE_BFLOAT16, 4, (char*)d_in[0] + PX, dims, strides, box, es, CU_TENSOR_MAP_INTERLEAVE_NONE,
           CU_TENSOR_MAP_SWIZZLE_NONE, CU_TENSOR_MAP_L2_PROMOTION_NONE, CU_TENSOR_MAP_FLOAT_OOB_FILL_NONE);
  }
  for (int i = 0; i < 2; i++) {
    const cuuint64_t dims[5] = {32, IC, 3, 3, 3};
    const cuuint64_t strides[4] = {IC * 2, 64, IC * IC * 2, 3 * IC * IC * 2};
    const cuuint32_t box[5] = {32, 16, 3, i ? 3u : 1u, i ? 1u : 3u};
    encode(&tm.w[i], CU_TENSOR_MAP_DATA_TYPE_BFLOAT16, 5, d_in[2], dims, strides, box, es, CU_TENSOR_MAP_INTERLEAVE_NONE,
           CU_TENSOR_MAP_SWIZZLE_64B, CU_TENSOR_MAP_L2_PROMOTION_L2_128B, CU_TENSOR_MAP_FLOAT_OOB_FILL_NONE);
  }
  for (int i = 0; i < 2; i++) {
    const cuuint64_t dims[2] = {IW * 9, IH};
    const cuuint64_t strides[1] = {IW * 36};
    const cuuint32_t box[2] = {i ? 72u : 144u, i ? 8u : 32u};
    encode(&tm.o[i], CU_TENSOR_MAP_DATA_TYPE_UINT32, 2, d_in[1], dims, strides, box, es, CU_TENSOR_MAP_INTERLEAVE_NONE,
           CU_TENSOR_MAP_SWIZZLE_NONE, CU_TENSOR_MAP_L2_PROMOTION_NONE, CU_TENSOR_MAP_FLOAT_OOB_FILL_NONE);
  }
  for (int i = 0; i < 4; i++) {
    const cuuint64_t dims[5] = {32, IW, i ? IH : 4u, i ? 1u : IH / 4, 3};
    const cuuint64_t strides[4] = {i == 2 ? ROW : PX, i == 2 ? PX : ROW, 4 * ROW, 64};
    const cuuint32_t box[5] = {32, 8, i == 3 ? 8u : i ? 16u : 1u, i ? 1u : 8u, 3};
    encode(&tm.out[i], CU_TENSOR_MAP_DATA_TYPE_BFLOAT16, 5, d_out, dims, strides, box, es, CU_TENSOR_MAP_INTERLEAVE_NONE,
           CU_TENSOR_MAP_SWIZZLE_64B, CU_TENSOR_MAP_L2_PROMOTION_NONE, CU_TENSOR_MAP_FLOAT_OOB_FILL_NONE);
  }
  dcn_kernel<<<GRID, NTHREADS, SMEM_BYTES>>>((const __nv_bfloat16*)d_in[0], (const uint32_t*)d_in[1], (const uint4*)d_in[2],
                                             (Scratch*)scratch, 0u, tm);
}
```

```cpp
#include <cuda_runtime.h>
#include <cuda.h>
#include <cuda_bf16.h>
#include <stdint.h>

namespace {

constexpr int IH = 224, IW = 224, IC = 96;
constexpr int GRID = 132, NC = 12, NW = 72, NG = 48;
constexpr int NTHREADS = 512;
constexpr int STAGE = 18432;
constexpr int WTAP = 3072 >> 4, WHALF = (STAGE / 2) >> 4;
constexpr uint32_t SB = 0x400;
constexpr int VROW = 18 * 64, VSLOT = 8 * VROW, PIECE = 34 * 128;
constexpr int SM_R = 14 * VSLOT, SM_WW = SM_R + 39936;
constexpr int GROW = 10 * 64, GSLICE = 20 * GROW, GWIN = 3 * GSLICE, SM_GW = 2 * GWIN, SM_GO = SM_GW + 7 * STAGE, SM_GT = SM_GO + 9216;
constexpr int CROW = 12 * 64, CSLICE = 12 * CROW, CWIN = 3 * CSLICE, SM_CX = 9 * STAGE, SM_CT = SM_CX + 2 * CWIN;
constexpr int SM_FIX = 224256, SM_BAR = 231168, SMEM_BYTES = 232448;
constexpr int B_XF = 0, B_PP = 15, B_WF = 16, B_IM = 34, B_OF = 35, B_SR = 36, B_P2 = 38, B_RD = 39, B_W2 = 96, B_OG = 7;
constexpr int B_WE = 40;
constexpr int B_WL = 56, B_V0 = 57, B_SG = 58, B_VE = 59;
constexpr int B_ST = 64, B_VF = 71, B_SW = 79, B_RE = 80, B_R2 = 85, B_FX = 86;
constexpr int O_TGT = 768, O_CNT = 776, O_REC = 784, O_SEL = 912, O_TIL = 976, O_TS = 1040;
constexpr int NREC = 16;
#define FP32T 0
#define BDELAY 1500
#define SDELAY 2600
#define FETCHN 4
#define BLENDN 3
#define PDELAY 4600
#define HOLD 0
#define SDELAY2 500
#define SWAIT 1
#define ODELAY 600
#define NPOLL 4
#define PSTEP 250
#define PF1 0
#define PF2 6000
#define PFS 500
#define PIN 1
#define FDELAY 7000
#define CW0 1500
#define CWS 300
#define CX0 1000
#define CXS 2500
#define BWAIT 1
#define UIST 0
#define PF0 0
#define ODDB 6
#define PQN 3
#define PPJ 0
#define CHUNK 8
#define NA0 5
#define WBOTH 1
#define LAFTER 0
#define XPRE 0
#define O1J 2
#define NS1 2
#define CPRED 0
#define GO0 1900
#define UDIRECT 0
#define UREL 0
#define XDELAY 0
#define SAFE 0
#define O0K 1
#define ADEF 2
#define WF32 0
#define DRY 1
#define P1J 4
#define P1K 0
#define HOLD2 1
#define P2J 0
#define WFORM 4
#define PPP 3
#define ROT 12
#define DIRECT 0
#define LEAN 1
#define TB 1
#define GTOP 0
#define OPER 2
#define GXS1 2300
#define LATE1 0
#define GX0 1500
#define GX1 3200
#define GXS 2300
#define GW0 1600
#define GWS 750
constexpr float PA = FP32T ? 2.0f / 3.0f : 0.5f, PB = FP32T ? 1.5f : 2.0f;
constexpr float AL = 1.0f - PA * PA / (PB * PB);

struct Scratch {
  uint8_t u[8 * STAGE];
  uint4 fix[8 * NREC * 12];
  uint2 key[8 * NREC];
  uint32_t cnt[32];
  uint32_t launch[160];
};
__device__ __align__(128) Scratch g_scratch;
#define TS(slot, i)
#define TS1(slot, i)
#define TSS(slot, i)
#define TSDUMP(slot)

__device__ __forceinline__ float bf16lo(uint32_t v) { return __uint_as_float(v << 16); }
__device__ __forceinline__ float bf16hi(uint32_t v) { return __uint_as_float(v & 0xffff0000u); }
__device__ __forceinline__ uint32_t smem_u32(const void* p) { return (uint32_t)__cvta_generic_to_shared(p); }
__device__ __forceinline__ void mbar_init(uint32_t bar, uint32_t count) {
  asm volatile("mbarrier.init.shared::cta.b64 [%0], %1;\n" ::"r"(bar), "r"(count) : "memory");
}
__device__ __forceinline__ void mbar_expect_tx(uint32_t bar, uint32_t bytes) {
  asm volatile("mbarrier.arrive.expect_tx.shared::cta.b64 _, [%0], %1;\n" ::"r"(bar), "r"(bytes) : "memory");
}
__device__ __forceinline__ void mbar_wait(uint32_t bar, uint32_t parity = 0) {
  asm volatile(
      "{\n.reg .pred p;\n"
      "W_%=:\n"
      "mbarrier.try_wait.parity.shared::cta.b64 p, [%0], %1;\n"
      "@!p pmevent 1;\n"
      "@!p bra W_%=;\n}\n"
      ::"r"(bar), "r"(parity) : "memory");
}
__device__ __forceinline__ uint32_t mbar_poll(uint32_t bar) {
  uint32_t done;
  asm volatile(
      "{\n.reg .pred p;\n"
      "mbarrier.test_wait.parity.shared::cta.b64 p, [%1], 0;\n"
      "selp.u32 %0, 1, 0, p;\n}\n"
      : "=r"(done)
      : "r"(bar)
      : "memory");
  return done;
}
__device__ __forceinline__ bool mbar_test(uint32_t bar) {
  uint32_t done;
  asm volatile(
      "{\n.reg .pred p;\n"
      "mbarrier.test_wait.parity.shared::cta.b64 p, [%1], 0;\n"
      "selp.u32 %0, 1, 0, p;\n}\n"
      : "=r"(done)
      : "r"(bar)
      : "memory");
  return __all_sync(0xffffffffu, done);
}
__device__ __forceinline__ uint32_t clock32() {
  uint32_t c;
  asm volatile("mov.u32 %0, %%clock;\n" : "=r"(c)::"memory");
  return c;
}
__device__ __forceinline__ int lane_now() {
  int l;
  asm volatile("mov.u32 %0, %%laneid;\n" : "=r"(l));
  return l;
}
__device__ __forceinline__ void wait_until(uint32_t t0, uint32_t dt) {
  while (clock32() - t0 < dt) __nanosleep(40);
}
__device__ __forceinline__ void tma_load_x(uint32_t dst, const CUtensorMap* tm, uint32_t bar, uint32_t bytes, int c0, int c1, int c2) {
  if (bytes) mbar_expect_tx(bar, bytes);
  asm volatile(
      "cp.async.bulk.tensor.3d.shared::cluster.global.mbarrier::complete_tx::bytes [%0], [%1, {%3, %4, %5}], [%2];\n" ::"r"(dst),
      "l"(reinterpret_cast<uint64_t>(tm)), "r"(bar), "r"(c0), "r"(c1), "r"(c2)
      : "memory");
}
__device__ __forceinline__ void tma_load_x4(uint32_t dst, const CUtensorMap* tm, uint32_t bar, int c, int y, int pair) {
  asm volatile(
      "cp.async.bulk.tensor.4d.shared::cluster.global.mbarrier::complete_tx::bytes [%0], [%1, {%3, %6, %4, %5}], [%2];\n" ::"r"(dst),
      "l"(reinterpret_cast<uint64_t>(tm)), "r"(bar), "r"(c), "r"(y), "r"(pair), "r"(0)
      : "memory");
}
__device__ __forceinline__ void tma_load_o(uint32_t dst, const CUtensorMap* tm, uint32_t bar, int x, int y) {
  asm volatile(
      "cp.async.bulk.tensor.2d.shared::cluster.global.mbarrier::complete_tx::bytes [%0], [%1, {%3, %4}], [%2];\n" ::"r"(dst),
      "l"(reinterpret_cast<uint64_t>(tm)), "r"(bar), "r"(x * 9), "r"(y)
      : "memory");
}
__device__ __forceinline__ void tma_load_w(uint32_t dst, const CUtensorMap* tm, uint32_t bar, int c, int kj, int ki, uint32_t mask) {
  asm volatile(
      "cp.async.bulk.tensor.5d.shared::cluster.global.mbarrier::complete_tx::bytes.multicast::cluster [%0], [%1, {%3, %4, "
      "%3, %5, %6}], [%2], %7;\n" ::"r"(dst),
      "l"(reinterpret_cast<uint64_t>(tm)), "r"(bar), "r"(0), "r"(c), "r"(kj), "r"(ki), "h"((uint16_t)mask)
      : "memory");
}
__device__ __forceinline__ void bulk_load_mc(uint32_t dst, const void* src, uint32_t bytes, uint32_t bar) {
  asm volatile(
      "cp.async.bulk.shared::cluster.global.mbarrier::complete_tx::bytes.multicast::cluster [%0], [%1], %2, [%3], %4;\n" ::"r"(dst),
      "l"(src), "r"(bytes), "r"(bar), "h"((uint16_t)3)
      : "memory");
}
__device__ __forceinline__ void tma_store(const CUtensorMap* tm, uint32_t src, int c1, int c2, int c3) {
  asm volatile("cp.async.bulk.tensor.5d.global.shared::cta.bulk_group [%0, {%2, %3, %4, %5, %2}], [%1];\n" ::"l"(
                   reinterpret_cast<uint64_t>(tm)),
               "r"(src), "r"(0), "r"(c1), "r"(c2), "r"(c3)
               : "memory");
  asm volatile("cp.async.bulk.commit_group;\n" ::: "memory");
}
__device__ __forceinline__ constexpr uint64_t w_desc(uint32_t saddr) {
  return (uint64_t)((saddr & 0x3FFFF) >> 4) | ((uint64_t)(1024 >> 4) << 16) | ((uint64_t)(512 >> 4) << 32) | ((uint64_t)2 << 62);
}
__device__ __forceinline__ constexpr uint64_t a_desc(uint32_t saddr) {
  return (uint64_t)((saddr & 0x3FFFF) >> 4) | ((uint64_t)1 << 16) | ((uint64_t)(VROW >> 4) << 32) | ((uint64_t)2 << 62);
}
#define ACC_OPERANDS(c, d)                                                                                        \
  c(d[0]), c(d[1]), c(d[2]), c(d[3]), c(d[4]), c(d[5]), c(d[6]), c(d[7]), c(d[8]),      \
      c(d[9]), c(d[10]), c(d[11]), c(d[12]), c(d[13]), c(d[14]), c(d[15]), c(d[16]),       \
      c(d[17]), c(d[18]), c(d[19]), c(d[20]), c(d[21]), c(d[22]), c(d[23]), c(d[24]),      \
      c(d[25]), c(d[26]), c(d[27]), c(d[28]), c(d[29]), c(d[30]), c(d[31]), c(d[32]),      \
      c(d[33]), c(d[34]), c(d[35]), c(d[36]), c(d[37]), c(d[38]), c(d[39]), c(d[40]),      \
      c(d[41]), c(d[42]), c(d[43]), c(d[44]), c(d[45]), c(d[46]), c(d[47])
#define ACC_LIST                                                                   \
  "{%0, %1, %2, %3, %4, %5, %6, %7, %8, %9, %10, %11, %12, %13, %14, %15, "        \
  "%16, %17, %18, %19, %20, %21, %22, %23, %24, %25, %26, %27, %28, %29, %30, %31, " \
  "%32, %33, %34, %35, %36, %37, %38, %39, %40, %41, %42, %43, %44, %45, %46, %47}, "
__device__ __forceinline__ void wgmma_ss(float* d, uint64_t adesc, uint64_t bdesc, uint32_t accumulate) {
  asm volatile(
      "{\n.reg .pred p;\nsetp.ne.b32 p, %50, 0;\n"
      "wgmma.mma_async.sync.aligned.m64n96k16.f32.bf16.bf16 " ACC_LIST "%48, %49, p, 1, 1, 0, 1;\n}\n"
      : ACC_OPERANDS("+f", d)
      : "l"(adesc), "l"(bdesc), "r"(accumulate));
}
__device__ __forceinline__ void wgmma_def(float* d, uint64_t desc, uint32_t on) {
  asm volatile(
      "{\n.reg .pred p, q;\nsetp.ne.b32 p, 0, 0;\nsetp.ne.b32 q, %49, 0;\n"
      "@q wgmma.mma_async.sync.aligned.m64n96k16.f32.bf16.bf16 " ACC_LIST "%48, %48, p, 1, 1, 1, 1;\n}\n"
      : ACC_OPERANDS("=f", d)
      : "l"(desc), "r"(on));
}
__device__ __forceinline__ void wgmma_rs(float* d, const uint32_t* a, uint64_t bdesc) {
  asm volatile(
      "{\n.reg .pred p;\nsetp.ne.b32 p, 1, 0;\n"
      "wgmma.mma_async.sync.aligned.m64n96k16.f32.bf16.bf16 " ACC_LIST "{%48, %49, %50, %51}, %52, p, 1, 1, 1;\n}\n"
      : ACC_OPERANDS("+f", d)
      : "r"(a[0]), "r"(a[1]), "r"(a[2]), "r"(a[3]), "l"(bdesc));
}
__device__ __forceinline__ void wgmma_fence() { asm volatile("wgmma.fence.sync.aligned;\n" ::: "memory"); }
__device__ __forceinline__ void wgmma_commit() { asm volatile("wgmma.commit_group.sync.aligned;\n" ::: "memory"); }
template <int N>
__device__ __forceinline__ void wgmma_wait() { asm volatile("wgmma.wait_group.sync.aligned %0;\n" ::"n"(N) : "memory"); }
__device__ __forceinline__ void acc_fence(float* d) {
#pragma unroll
  for (int i = 0; i < 48; i++) asm volatile("" : "+f"(d[i])::"memory");
}
#define UPD(text, d, e, c) asm volatile("{\n.reg .pred p;\nsetp.eq.u32 p, %3, 0;\n@p " text ";\n}\n" : "+f"(d) : "f"(e), "f"(c), "r"(guard))
#define UPD_ADD(d, e, c) UPD("fma.rn.f32 %0, %1, %2, %0", d, e, c)
#define UPD_MUL(d, e, c) UPD("fma.rn.f32 %0, %0, %2, %1", d, e, c)
#define UPD_SCL(d, c) UPD("mul.f32 %0, %0, %2", d, c, c)
__device__ __forceinline__ void keep_alive8(const uint32_t* a, uint32_t never) {
  asm volatile(
      "{\n.reg .pred p, q;\nsetp.eq.u32 p, %8, 16;\nsetp.eq.u32 q, %8, 32;\n"
      "@p st.shared.v4.b32 [%8], {%0, %1, %2, %3};\n@q st.shared.v4.b32 [%8], {%4, %5, %6, %7};\n}\n" ::"r"(a[0]),
      "r"(a[1]), "r"(a[2]), "r"(a[3]), "r"(a[4]), "r"(a[5]), "r"(a[6]), "r"(a[7]), "r"(never)
      : "memory");
}
__device__ __forceinline__ void keep_alive4(const uint32_t* a, uint32_t never) {
  asm volatile("{\n.reg .pred p;\nsetp.eq.u32 p, %4, 16;\n@p st.shared.v4.b32 [%4], {%0, %1, %2, %3};\n}\n" ::"r"(a[0]), "r"(a[1]), "r"(a[2]),
               "r"(a[3]), "r"(never) : "memory");
}
__device__ __forceinline__ void ldsm4(uint32_t& r0, uint32_t& r1, uint32_t& r2, uint32_t& r3, uint32_t addr) {
  asm volatile("ldmatrix.sync.aligned.m8n8.x4.shared.b16 {%0, %1, %2, %3}, [%4];\n"
               : "=r"(r0), "=r"(r1), "=r"(r2), "=r"(r3)
               : "r"(addr)
               : "memory");
}
__device__ __forceinline__ void ldsm4(uint32_t* r, uint32_t addr) { ldsm4(r[0], r[1], r[2], r[3], addr); }
__device__ __forceinline__ void arrive_if(uint32_t bar) {
  asm volatile("{\n.reg .pred p;\nsetp.ne.u32 p, %0, 0;\n@p mbarrier.arrive.shared::cluster.b64 _, [%0];\n}\n" ::"r"(bar) : "memory");
}
__device__ __forceinline__ uint32_t lds32(uint32_t addr) {
  uint32_t v;
  asm volatile("ld.shared.u32 %0, [%1];\n" : "=r"(v) : "r"(addr) : "memory");
  return v;
}
__device__ __forceinline__ void lds64(uint32_t& a, uint32_t& b, uint32_t addr) {
  asm volatile("ld.shared.v2.u32 {%0, %1}, [%2];\n" : "=r"(a), "=r"(b) : "r"(addr) : "memory");
}
__device__ __forceinline__ void lds128(uint32_t* v, uint32_t addr) {
  asm volatile("ld.shared.v4.b32 {%0, %1, %2, %3}, [%4];\n" : "=r"(v[0]), "=r"(v[1]), "=r"(v[2]), "=r"(v[3]) : "r"(addr) : "memory");
}
__device__ __forceinline__ void sts128(uint32_t addr, const uint32_t* v) {
  asm volatile("st.shared.v4.b32 [%0], {%1, %2, %3, %4};\n" ::"r"(addr), "r"(v[0]), "r"(v[1]), "r"(v[2]), "r"(v[3]) : "memory");
}
__device__ __forceinline__ void sts64(uint32_t addr, const uint32_t* v) {
  asm volatile("st.shared.v2.b32 [%0], {%1, %2};\n" ::"r"(addr), "r"(v[0]), "r"(v[1]) : "memory");
}
__device__ __forceinline__ void sts32(uint32_t addr, uint32_t v) {
  asm volatile("st.shared.u32 [%0], %1;\n" ::"r"(addr), "r"(v) : "memory");
}
__device__ __forceinline__ void fence_async() { asm volatile("fence.proxy.async.shared::cta;\n" ::: "memory"); }
__device__ __forceinline__ void bar_sync(int id, int n) { asm volatile("bar.sync %0, %1;\n" ::"r"(id), "r"(n) : "memory"); }
__device__ __forceinline__ __nv_bfloat162 as_bf2(uint32_t v) { return *reinterpret_cast<__nv_bfloat162*>(&v); }
__device__ __forceinline__ uint32_t as_u32(__nv_bfloat162 v) { return *reinterpret_cast<uint32_t*>(&v); }
__device__ __forceinline__ uint32_t hfma2(uint32_t c, uint32_t a, uint32_t b) { return as_u32(__hfma2(as_bf2(c), as_bf2(a), as_bf2(b))); }
__device__ __forceinline__ uint32_t hadd2(uint32_t a, uint32_t b) { return as_u32(__hadd2(as_bf2(a), as_bf2(b))); }
__device__ __forceinline__ uint32_t hsub2(uint32_t a, uint32_t b) { return as_u32(__hsub2(as_bf2(a), as_bf2(b))); }
__device__ __forceinline__ __nv_bfloat162 half_of(uint32_t w, int hi) { return hi ? __high2bfloat162(as_bf2(w)) : __low2bfloat162(as_bf2(w)); }
__device__ __forceinline__ uint32_t hmul2_h(uint32_t w, int hi, uint32_t a) { return as_u32(__hmul2(half_of(w, hi), as_bf2(a))); }
__device__ __forceinline__ uint32_t hfma2_h(uint32_t w, int hi, uint32_t a, uint32_t c) {
  return as_u32(__hfma2(half_of(w, hi), as_bf2(a), as_bf2(c)));
}
__device__ __forceinline__ uint32_t pack2(float lo, float hi) { return as_u32(__floats2bfloat162_rn(lo, hi)); }
__device__ __forceinline__ uint32_t prmt(uint32_t a, uint32_t b, uint32_t sel) {
  uint32_t r;
  asm("prmt.b32 %0, %1, %2, %3;\n" : "=r"(r) : "r"(a), "r"(b), "r"(sel));
  return r;
}
__device__ __forceinline__ uint32_t absmax2(uint32_t a, uint32_t b) {
  uint32_t r;
  asm("max.NaN.xorsign.abs.bf16x2 %0, %1, %2;\n" : "=r"(r) : "r"(a), "r"(b));
  return r;
}
__device__ __forceinline__ uint32_t clip2(uint32_t p) {
  return as_u32(__hmin2(__hmax2(as_bf2(p), as_bf2(0u)), as_bf2(0x435f435fu)));
}
__device__ __forceinline__ constexpr uint32_t tap_delta(int a, int b) {
  return (a == 0 ? 0xbf80u : a == 1 ? 0u : 0x3f80u) | (b == 0 ? 0xbf800000u : b == 1 ? 0u : 0x3f800000u);
}
__device__ __forceinline__ void coefs(uint32_t w, uint32_t& p0, uint32_t& p1) {
  const uint32_t o = hsub2(0x3f803f80u, w);
  const uint32_t xa = __byte_perm(o, w, 0x7632);
  p0 = hmul2_h(o, 0, xa);
  p1 = hmul2_h(w, 0, xa);
}
__device__ __forceinline__ uint32_t frac2(uint32_t pos) {
  const float py = bf16lo(pos), px = bf16hi(pos);
  return __byte_perm(__float_as_uint(py - floorf(py)), __float_as_uint(px - floorf(px)), 0x7632);
}
__device__ __forceinline__ void blend4(uint32_t* t, const uint32_t* g, const uint32_t* h, const uint32_t* k, uint32_t a0,
                                       uint32_t a1, uint32_t b0, uint32_t b1) {
#pragma unroll
  for (int i = 0; i < 4; i++) {
    const uint32_t p0 = (i & 1) ? b0 : a0, p1 = (i & 1) ? b1 : a1;
    t[i] = hfma2_h(p1, 1, k[i], hfma2_h(p1, 0, h[i], hfma2_h(p0, 1, g[i], hmul2_h(p0, 0, t[i]))));
  }
}
__device__ __forceinline__ bool elect_one() {
  uint32_t r;
  asm volatile("{\n.reg .pred p;\nelect.sync _|p, 0xffffffff;\nselp.u32 %0, 1, 0, p;\n}\n" : "=r"(r));
  return r != 0;
}

template <int N>
__device__ __forceinline__ void transform6(const uint32_t (*d)[N], uint32_t dst, uint32_t off0) {
  uint32_t v[N], t[N], u[N];
  auto put = [&](int slot, const uint32_t* r) {
    const uint32_t a = slot < 4 ? dst + slot * VSLOT : dst + off0 + (slot - 4) * VSLOT;
    if (N == 4) sts128(a, r);
    else sts64(a, r);
  };
#pragma unroll
  for (int k = 0; k < 2; k++) {
#pragma unroll
    for (int i = 0; i < N; i++) v[i] = hfma2(0xc088c088u, d[2 + k][i], hadd2(d[k][i], d[4 + k][i]));
    put(4 + k, v);
  }
#pragma unroll
  for (int k = 0; k < 2; k++) {
    const uint32_t c = k ? 0xbe80be80u : 0xc080c080u, f = k ? 0x40004000u : 0x3f003f00u;
#pragma unroll
    for (int i = 0; i < N; i++) {
      t[i] = hfma2(c, d[2][i], d[4][i]);
      u[i] = hfma2(c, d[1][i], d[3][i]);
      v[i] = hfma2(f, u[i], t[i]);
    }
    put(2 * k, v);
#pragma unroll
    for (int i = 0; i < N; i++) t[i] = hfma2(f ^ 0x80008000u, u[i], t[i]);
    put(2 * k + 1, t);
  }
}

__device__ __forceinline__ void weights4(const uint32_t* g0, const uint32_t* g1, const uint32_t* g2, uint32_t (*u)[4]) {
#pragma unroll
  for (int i = 0; i < 4; i++) {
    const uint32_t ea = hfma2(0xbe00be00u, g2[i], as_u32(__hmul2(as_bf2(g0[i]), as_bf2(0xbf00bf00u)))), eb = hfma2(0x3e803e80u, g0[i], g2[i]);
    u[0][i] = hfma2(0xbe80be80u, g1[i], ea);
    u[1][i] = hfma2(0x3e803e80u, g1[i], ea);
    u[2][i] = hfma2(0x3f003f00u, g1[i], eb);
    u[3][i] = hfma2(0xbf00bf00u, g1[i], eb);
  }
}

template <int GROUP = 4096, bool SCALE = false>
__device__ __forceinline__ void stage_slab(const float* acc, uint32_t stg, int lane, uint32_t skip = 0) {
  const uint32_t a = stg + (lane & 15) * 64 + (((lane >> 4) ^ ((lane >> 1) & 3)) << 4);
#pragma unroll
  for (int jp = 0; jp < 6; jp++) {
    uint32_t pk[4];
#pragma unroll
    for (int i = 0; i < 4; i++) {
      constexpr float f = SCALE ? 8.0f / 15.0f : 1.0f;
      pk[i] = pack2(acc[jp * 8 + i * 2] * f, acc[jp * 8 + i * 2 + 1] * f);
    }
    asm volatile("{\n.reg .pred p;\nsetp.eq.u32 p, %5, 0;\n@p stmatrix.sync.aligned.m8n8.x4.shared.b16 [%0], {%1, %2, %3, %4};\n}\n" ::"r"(
                     (a ^ ((jp & 1) * 32)) + (jp >> 1) * GROUP),
                 "r"(pk[0]), "r"(pk[1]), "r"(pk[2]), "r"(pk[3]), "r"(skip)
                 : "memory");
  }
}
__device__ __forceinline__ void publish(uint32_t bar, int lane) {
  fence_async();
  __syncwarp();
  arrive_if(lane == 0 ? bar : 0u);
}
__device__ __forceinline__ constexpr uint32_t w_slot(int st) {
  return st < 3 ? SM_WW + st * STAGE : st == 3 ? 12 * VSLOT : st < 11 ? SM_WW + (st - 4) % 3 * STAGE : st < 13 ? 4 * VSLOT + (st - 11) * STAGE
         : st < 16 ? SM_WW + st % 3 * STAGE : st == 16 ? 4 * VSLOT : STAGE;
}
__device__ __forceinline__ constexpr uint64_t w_slots(int st0, int step, int n) {
  uint64_t r = 0;
  for (int i = 0; i < n; i++) r |= (uint64_t)(w_slot(st0 + i * step) >> 10) << (8 * i);
  return r;
}
__device__ __forceinline__ uint32_t w_stg(int wg, int i) {
  return wg ? (i == 2 ? SM_R + 24576 : i == 1 ? 0 : i == 0 ? 4 * VSLOT + STAGE : SM_WW + STAGE) : SM_R + (i & 1) * 12288;
}

__device__ __forceinline__ void ldsm4_if(uint32_t* r, uint32_t addr, uint32_t on) {
  asm volatile(
      "{\n.reg .pred p;\nsetp.ne.u32 p, %5, 0;\n"
      "@p ldmatrix.sync.aligned.m8n8.x4.shared.b16 {%0, %1, %2, %3}, [%4];\n}\n"
      : "+r"(r[0]), "+r"(r[1]), "+r"(r[2]), "+r"(r[3])
      : "r"(addr), "r"(on)
      : "memory");
}
__device__ __forceinline__ void push_record(uint32_t bars, uint32_t key, uint32_t pos) {
  uint32_t slot;
  asm volatile("atom.shared.add.u32 %0, [%1], 1;\n" : "=r"(slot) : "r"(bars + O_CNT) : "memory");
  const uint32_t v[2] = {key, pos};
  if (slot < NREC) sts64(bars + O_REC + slot * 8, v);
}
__device__ __forceinline__ void put_sel(uint32_t bars, uint32_t key, int lane) {
  if (lane < NREC)
    asm volatile("st.shared.u16 [%0], %1;\n" ::"r"(bars + O_SEL + (lane & 6) * 4 + (lane >> 3) * 4 + (lane & 1) * 2), "h"((uint16_t)((key >> 20) | 0x4000u)) : "memory");
}
__device__ __noinline__ void push_taps(uint32_t bars, uint32_t key, uint32_t taps, const uint32_t* __restrict__ offs) {
  const int y = key & 255, x = (key >> 8) & 255;
#pragma unroll 1
  for (; taps; taps &= taps - 1) {
    const int tap = __ffs(taps) - 1, ki = (tap * 11) >> 5;
    const uint32_t gp = pack2((float)(y + ki - 1), (float)(x + tap - ki * 3 - 1));
    push_record(bars, key | (tap << 16), clip2(hadd2(gp, __ldg(offs + (y * IW + x) * 9 + tap))));
  }
}
__device__ __forceinline__ uint32_t wino_key(int y, int x) {
  return y | (x << 8) | ((((y & 28) << 1) | (x & 7)) << 20) | ((((x & 8) >> 1) | (y & 3)) << 27);
}
__device__ __forceinline__ uint32_t strip_key(int u, int v, int left) {
  return (left ? v | (u << 8) : u | (v << 8)) | ((((u & 15) << 3) | (v & 7)) << 20) | ((u >> 4) << 29);
}
__device__ __forceinline__ bool strip_off(uint32_t d, bool out) { return (d & 0x7fff) || (d & 0x7fff7fffu) > (out ? 0u : 0x3f000000u); }
__device__ __forceinline__ void delta(uint32_t* v, uint32_t key, uint32_t pos, const uint4* __restrict__ x, int c) {
  const int tap = (key >> 16) & 15, ki = (tap * 11) >> 5, gy = (int)bf16lo(pos), gx = (int)bf16hi(pos);
  const int cy = min(max((int)(key & 255) + ki - 1, 0), IH - 1), cx = min(max((int)((key >> 8) & 255) + tap - ki * 3 - 1, 0), IW - 1);
  const uint32_t sx = gx < IW - 1 ? 12 : 0, sy = gy < IH - 1 ? IW * 12 : 0, p = (gy * IW + gx) * 12 + c;
  uint4 t[5] = {__ldg(x + p), __ldg(x + (p + sx)), __ldg(x + (p + sy)), __ldg(x + (p + sy + sx)), __ldg(x + (uint32_t)((cy * IW + cx) * 12 + c))};
  uint32_t q0, q1;
  coefs(frac2(pos), q0, q1);
  blend4(&t[0].x, &t[1].x, &t[2].x, &t[3].x, q0, q1, q0, q1);
#pragma unroll
  for (int i = 0; i < 4; i++) v[i] = hsub2((&t[0].x)[i], (&t[4].x)[i]);
}
__device__ __forceinline__ void fixup(uint32_t bars, int w, int n, const uint4* __restrict__ x, const uint4* __restrict__ wgt) {
  const uint32_t fix = bars + SM_FIX - SM_BAR + 3072, part = fix + 3072;
  const int lane = lane_now(), l = min(lane, 23), up = l >= 12;
#pragma unroll
  for (int i = 0; i < 6; i++) sts32(fix + (i * 128 + w * 32 + lane) * 4, 0);
#pragma unroll 1
  for (int r = 0; r < n; r++) {
    uint32_t key, pos, sum[4];
    lds64(key, pos, bars + O_REC + r * 8);
    key = __shfl_sync(0xffffffffu, key, 0);
    pos = __shfl_sync(0xffffffffu, pos, 0);
    delta(sum, key, pos, x, w * 3 + (l >> 3));
    sts128(part + w * 192 + (l >> 3) * 16, sum);
    __syncwarp();
#pragma unroll
    for (int i = 0; i < 4; i++) sum[i] = 0;
    const uint4* wp = wgt + (((key >> 16) & 15) * 96 + w * 24 + up * 11) * 12 + l;
#pragma unroll 1
    for (int h = 0; h < 3; h++) {
      uint4 wv[4];
      uint32_t d[2];
#pragma unroll
      for (int k = 0; k < 4; k++) wv[k] = __ldg(wp + (h * 4 + k) * 12);
      lds64(d[0], d[1], part + w * 192 + up * 24 + h * 8);
#pragma unroll
      for (int i = 0; i < 4; i++)
        sum[i] = hadd2(sum[i], hfma2_h(d[1], 1, (&wv[3].x)[i], hfma2_h(d[1], 0, (&wv[2].x)[i], hfma2_h(d[0], 1, (&wv[1].x)[i], hmul2_h(d[0], 0, (&wv[0].x)[i])))));
    }
#pragma unroll
    for (int i = 0; i < 4; i++) sum[i] = hadd2(sum[i], __shfl_down_sync(0xffffffffu, sum[i], 12));
    if (lane < 12) sts128(part + w * 192 + lane * 16, sum);
    bar_sync(4, 128);
    if (lane < 12) {
      float lo = 0.0f, hi = 0.0f;
#pragma unroll
      for (int k = 0; k < 4; k++) {
        const uint32_t v = lds32(part + k * 192 + w * 48 + lane * 4);
        lo += bf16lo(v);
        hi += bf16hi(v);
      }
      const int c = w * 12 + lane;
      sts32(fix + (c >> 4) * 1024 + r * 64 + ((((c >> 2) ^ (r >> 1)) & 3) << 4) + (c & 3) * 4, pack2(lo, hi));
    }
    bar_sync(4, 128);
  }
}
__device__ __forceinline__ void select_rows(uint32_t* A, const uint32_t* sel, uint32_t code, bool scale) {
#pragma unroll
  for (int i = 0; i < 4; i++) {
    A[i] = as_u32(__heq2(as_bf2(sel[i >> 1]), as_bf2(code + (i & 1) * 0x80008u)));
    if (scale) A[i] = as_u32(__hmul2(as_bf2(A[i]), as_bf2(0x3ff03ff0u)));
  }
}
template <int N>
__device__ __forceinline__ void correct(float (*acc)[48], uint32_t bars, uint32_t tiles, uint32_t code, int lane) {
#pragma unroll 1
  for (uint32_t b = 0; tiles & 0xf0fu; b++, tiles >>= 8) {
    uint32_t sel[2];
    lds64(sel[0], sel[1], bars + O_SEL + b * 32 + (lane & 3) * 8);
    asm volatile("" : "+r"(code));
#pragma unroll
    for (int p = 0; p < N; p++) {
      if (!((tiles >> (N == 4 ? p : 0)) & 1)) continue;
      uint32_t A[4];
      select_rows(A, sel, code + p * (N == 4 ? 0x800080u : 0x100010u), N == 4 && (p == 1 || p == 2));
      wgmma_fence();
      wgmma_rs(acc[p], A, w_desc(SB + SM_FIX) + b * (3072 >> 4));
      wgmma_commit();
      wgmma_wait<0>();
    }
  }
}

struct Maps {
  CUtensorMap x[5];
  CUtensorMap w[2];
  CUtensorMap o[2];
  CUtensorMap out[5];
};

__global__ void __cluster_dims__(2, 1, 1) __launch_bounds__(NTHREADS, 1)
dcn_kernel(const __nv_bfloat16* __restrict__ x, const uint32_t* __restrict__ offs, const uint4* __restrict__ wgt, Scratch* scr,
           const uint32_t never, const __grid_constant__ Maps tm) {
  extern __shared__ __align__(1024) uint8_t smem[];
  const uint32_t sbase = smem_u32(smem);
  const uint32_t bars = sbase + SM_BAR;
  const uint32_t tstart = clock32();
  const int tid = threadIdx.x;
  const int cta = blockIdx.x - NC;
  const int wid = __shfl_sync(0xffffffffu, tid >> 5, 0);
  const int lane = tid & 31;
  const bool wino = (uint32_t)cta < NW, strip = cta >= NW;
  const int left = (uint32_t)cta >= NW + NG / 2;
  const int ry = (cta * 43) >> 9;
  const int x0 = wino ? 32 + (cta - ry * 12) * 16 : 32 + (cta - NW - left * (NG / 2)) * 8, y0 = 32 + ry * 32;
  auto load_cols = [&](int s, int j) {
    const uint32_t dst = sbase + (s ? SM_R : 4 * VSLOT) + j * 2 * PIECE, bar = bars + (B_XF + s * 5 + j) * 8;
    if (j < 4) tma_load_x4(dst, &tm.x[4], bar, s * 32, y0 - 1, (x0 >> 1) - 1 + j * 2);
    else tma_load_x(dst, &tm.x[0], bar, 0, s * 32, x0 + 15, y0 - 1);
  };
  auto corner_tile = [&](int wg) {
    const uint32_t t = ((wg ? 0xfbea00000000ull : 0xdc7398265410ull) >> (4 * (cta + NC))) & 15;
    return (t & 3) | ((t >> 2) << 8);
  };
  const bool one = elect_one();
  if (wid == 0 && one) {
    asm volatile("prefetch.tensormap [%0];\n" ::"l"(reinterpret_cast<uint64_t>(wino ? &tm.x[4] : &tm.o[1])) : "memory");
    asm volatile("prefetch.tensormap [%0];\n" ::"l"(reinterpret_cast<uint64_t>(&tm.x[0])) : "memory");
  }
  if (wid == 15) {
    if (one) {
      if (wino) {
        mbar_init(bars + B_W2 * 8, 1);
#pragma unroll
        for (int k = 0; k < 9; k++)
          asm volatile("cp.async.bulk.shared::cluster.global.mbarrier::complete_tx::bytes [%0], [%1], 6144, [%2];\n" ::"r"(sbase + k * 6144 + (k < 6 ? 0 : 6 * VSLOT)),
                       "l"(wgt + k * 1152), "r"(bars + B_W2 * 8) : "memory");
        TS(6, 26);
      }
#pragma unroll
      for (int j = 0; j < 8; j++) mbar_init(bars + j * 8, 1);
      if (wino) {
#pragma unroll
        for (int j = 0; j < NA0; j++) load_cols(0, j);
        mbar_expect_tx(bars + B_W2 * 8, 9 * 6144);
      } else {
        mbar_expect_tx(bars + B_OG * 8, strip ? 4 * 2304 : 2 * 2304);
#pragma unroll
        for (int k = 0; k < 4; k++) {
          const uint32_t tl = corner_tile(k & 1);
          if (strip || k < 2)
            tma_load_o(sbase + (strip ? SM_GO + k * 2304 : SM_CX + k * CWIN + 2 * CSLICE), &tm.o[1], bars + B_OG * 8,
                       strip ? (left ? k * 8 : x0) : (tl & 255) * 8, strip ? (left ? x0 : k * 8) : (tl >> 8) * 8);
        }
        if (GTOP && strip) {
#pragma unroll
          for (int r = 0; r < GTOP; r++)
            tma_load_x(sbase + r * GWIN, &tm.x[1 + left], bars + (B_XF + r * 3) * 8, GSLICE, 0, x0 - 1, r * 16 - 2);
        } else {
          asm volatile("prefetch.tensormap [%0];\n" ::"l"(reinterpret_cast<uint64_t>(&tm.x[strip ? 1 + left : 3])) : "memory");
        }
        asm volatile("prefetch.tensormap [%0];\n" ::"l"(reinterpret_cast<uint64_t>(&tm.w[left])) : "memory");
      }
      asm volatile("fence.mbarrier_init.release.cluster;\n" ::: "memory");
    }
    __syncwarp();
    TS(6, 25);
  }
  const bool prep = wid >= 8 && wid < 11 && strip && cta < NW + 24;
  uint4 g[3];
  if (prep) {
    const uint4* src = wgt + (uint32_t)((cta - NW + ((cta - NW) >> 3) * 4) * 96 + 352 + (tid >> 5) * 4 + (lane >> 2) * 12 + (lane & 3));
#pragma unroll
    for (int k = 0; k < 3; k++) g[k] = __ldg(src + k * 3456);
  }
  if (wid < 8 || wid >= 12) {
    if (one && wid < 15) {
      const int grp = wid < 8 ? 4 + wid : 15 - wid;
#pragma unroll
      for (int i = 0; i < 8; i++) mbar_init(bars + grp * 64 + i * 8, grp < 5 ? 1 : grp < 7 ? 16 : grp < 8 ? 8 : 4);
      asm volatile("fence.mbarrier_init.release.cluster;\n" ::: "memory");
    }
    __syncwarp();
  } else if (one) {
    if (wid == 11) {
      const uint32_t z[2] = {0, 1u << 31};
      sts64(bars + O_CNT, z);
      sts32(bars + O_TIL, 1u << 31);
      __threadfence_block();
    }
  }
  if (wid == 15) TS(6, 22);
  asm volatile("barrier.cluster.arrive.relaxed.aligned;\n" ::: "memory");
  auto load_cw = [&](int st) {
    const uint32_t rank = cta & 1;
    const int g = (st * 11) >> 5;
    const uint32_t fb = bars + (B_WF + st) * 8;
    mbar_expect_tx(fb, STAGE);
    tma_load_w(sbase + st * STAGE, &tm.w[1], fb, g * 32, 0, st - g * 3, 1u << rank);
    tma_load_w(sbase + st * STAGE + STAGE / 2, &tm.w[1], fb, g * 32 + 16, 0, st - g * 3, 1u << rank);
  };
  auto load_cx = [&](int wg, int g, uint32_t tl) {
    tma_load_x(sbase + SM_CX + wg * CWIN + g * CSLICE, &tm.x[3], bars + (B_XF + wg * 3 + g) * 8, CSLICE, g * 32, (int)(tl & 255) * 8 - 2,
               (int)(tl >> 8) * 8 - 2);
  };
  if (wid < 8) {
    const int wg = wid >> 2, warp = wid & 3, lane = lane_now();
    if ((sbase & 0xffffff) != SB) __trap();
    TSS(wg, 25);
    asm volatile("setmaxnreg.inc.sync.aligned.u32 224;\n");
    asm volatile("barrier.cluster.wait.acquire.aligned;\n" ::: "memory");
    TSS(wg, 26);
    uint32_t we_addr;
    asm volatile("mapa.shared::cluster.u32 %0, %1, %2;\n" : "=r"(we_addr) : "r"(bars + B_WE * 8), "r"(lane & 1));
    const uint32_t nv = never & (uint32_t)tid;
    float acc[4][48];
    int ntiles = 0;

    uint32_t tile0 = 0, tstep = 0;
    if (wino) {
      {
        const uint32_t dst = sbase + (wid & 2) * (STAGE / 4) + (wid & 1) * 512 + (lane >> 2) * 64 + (((lane ^ (lane >> 3)) & 3) << 4);
        const uint32_t src = sbase + warp * 1536 + (lane >> 2) * 192 + (lane & 3) * 16;
        mbar_wait(bars + B_W2 * 8);
        TSS(wg, 27);
        uint32_t gg[2][3][4];
        auto get = [&](int b, int n) {
          const uint32_t a = src + n * 64 + ((n * 11) >> 5) * (6144 - 192);
          lds128(gg[b][0], a);
          lds128(gg[b][2], a + 10 * VSLOT);
          lds128(gg[b][1], a + 18432);
        };
        auto put = [&](int b, int n) {
          uint32_t u[4][4];
          weights4(gg[b][0], gg[b][1], gg[b][2], u);
#pragma unroll
          for (int k = 0; k < 4; k++) sts128(dst + n * 1024 + w_slot(k), u[k]);
        };
        get(0, wg);
#pragma unroll 1
        for (int n = wg; n < 8; n += 4) {
          get(1, n + 2);
          put(0, n);
          get(0, min(n + 4, 8));
          put(1, n + 2);
        }
        if (!wg) put(0, 8);
        fence_async();
        bar_sync(12, 384);
      }
      TSS(wg, 23);
      {
        const int q = wid + wg, tp = lane >> 3, h = tp * 18 + q;
        const uint32_t src = (sbase + 4 * VSLOT + q * PIECE + tp * 1024 + (lane & 7) * 16) & (x0 + 2 * q == IW ? ~64u : ~0u);
        const uint32_t vb = sbase + h * 128 + (lane & 4) * 16;
        mbar_wait(bars + (B_XF + (q >> 1)) * 8);
        uint32_t d[10][4];
#pragma unroll
        for (int r = 0; r < 9; r++) lds128(d[r], src + r * 128);
        lds128(d[9], src + (y0 + 32 == IH && tp == 3 ? 8 * 128 : 9 * 128));
        transform6<4>(d, vb + (((lane ^ h) & 3) << 4), 10 * VSLOT);
        transform6<4>(d + 4, vb + VROW + (((lane ^ (h + 1)) & 3) << 4), 10 * VSLOT);
        publish(bars + (wg ? B_VF + 1 : B_V0) * 8, lane);
      }
      TSS(wg, 24);
      constexpr uint64_t bd0 = w_desc(SB);
      const uint64_t ad0 = a_desc(SB) + wg * 32;
      uint32_t rel = 0;
      if (lane == 3) we_addr = bars + (B_VE - 3) * 8;
      if (lane == 2) we_addr = bars + (B_WL - 13) * 8;
      uint32_t guard = never, gnext = never;
#define PIN_NEXT do { guard = gnext; gnext = clock32() & never; } while (0)
      auto stage = [&](float* a, int st, uint32_t rs, int vslot, uint32_t accumulate, auto work, bool retire = true, bool await = true) {
        const uint64_t bd = bd0 + (rs >> 4), ad = ad0 + vslot * (VSLOT >> 4);
        if (await) mbar_wait(bars + (B_WF + st) * 8);
        TSS(wg, st);
        wgmma_fence();
#pragma unroll
        for (int j = 0; j < 6; j++) {
          wgmma_ss(a, ad + (j >> 1) * 4 + (j & 1) * 2, bd + (j >> 1) * WTAP + (j & 1) * WHALF, j ? 1 : accumulate);
          if (j == 1 && retire) {
            wgmma_commit();
            wgmma_wait<1>();
            arrive_if(rel);
            rel = ((lane < 2 ? 0xff7u : lane == 3 ? 8u : lane == 2 ? 0x2000u : 0u) >> st) & 1 ? we_addr + st * 8 : 0u;
          }
          if (j == 5) wgmma_commit();
          work(j);
        }
      };
      {
#pragma unroll
        for (int p = 0; p < 4; p++) {
          wgmma_fence();
          wgmma_def(acc[p], w_desc(SB + SM_WW), ADEF == 1 ? 1 : never);
        }
        wgmma_commit();
      }
      mbar_wait(bars + B_V0 * 8);
      if (wg) mbar_wait(bars + (B_VF + 1) * 8);
#pragma unroll 1
      for (int s = 0; s < 3; s++) {
        if (s) {
          const uint32_t vf = bars + (B_VF + 2 * s + wg) * 8;
          if (!mbar_test(vf) || (PPP < 4 && wg && s == 2)) {
            wgmma_wait<0>();
            arrive_if(rel);
            rel = 0;
            mbar_wait(vf);
            if (PPP < 4 && wg && s == 2) mbar_wait(bars + B_PP * 8);
          }
        }
#pragma unroll
        for (int p = 0; p < 4; p++) {
          stage(acc[p], s * 4 + p, (((uint32_t)w_slots(p, 4, 3) >> (8 * s)) & 255) << 10, (s & 1) * 4 + p, s, [&](int j) {
            if (p == PPP && j == PPJ) arrive_if(tid == 0 && s == 2 ? bars + B_PP * 8 : 0u);
          });
        }
      }
      uint32_t imp = lds32(bars + O_CNT + 4);
#pragma unroll
      for (int i = 0; i < 48; i++) {
        if (i % CHUNK == 0) PIN_NEXT;
        UPD_ADD(acc[0][i], acc[1][i], 1.0f);
        UPD_MUL(acc[1][i], acc[0][i], -2.0f);
      }
      wgmma_wait<0>();
      arrive_if(rel);
      rel = 0;
      TSS(wg, 18);
      imp = __ballot_sync(0xffffffffu, (imp >> lane) & 1);
      uint32_t sel[2], A[4];
      if ((imp >> (wg * 4)) & ~0xf0f0u) {
        mbar_wait(bars + B_IM * 8);
        if ((int)imp < 0) imp = __ballot_sync(0xffffffffu, (lds32(bars + O_CNT + 4) >> lane) & 1);
        lds64(sel[0], sel[1], bars + O_SEL + (lane & 3) * 8);
      }
      imp >>= wg * 4;
      const uint32_t code = (wg * 512 + warp * 16 + (lane >> 2) + 0x4000u) * 0x10001u;
      auto corr = [&](int p, uint32_t* A) {
#pragma unroll
        for (int i = 0; i < 4; i++) asm volatile("mov.b32 %0, 0;\n" : "=r"(A[i]));
        if ((imp >> p) & 1) {
          select_rows(A, sel, code + p * 0x800080u, p == 1 || p == 2);
          wgmma_fence();
          wgmma_rs(acc[p], A, w_desc(SB + SM_FIX));
          wgmma_commit();
        }
      };
      auto done = [&] {
        wgmma_wait<0>();
        keep_alive4(A, nv);
      };
#pragma unroll
      for (int i = 0; i < 48; i++) {
        if (i % CHUNK == 0) PIN_NEXT;
        UPD_ADD(acc[2][i], acc[3][i], 1.0f);
        UPD_MUL(acc[3][i], acc[2][i], -2.0f);
        UPD_ADD(acc[2][i], acc[0][i], 0.5f);
        UPD_ADD(acc[0][i], acc[2][i], 2.0f / 15.0f);
      }
      corr(2, A);
      uint32_t tiles = lds32(bars + O_TIL);
#pragma unroll
      for (int i = 0; i < 48; i++) {
        if (i % (2 * CHUNK) == 0) PIN_NEXT;
        UPD_ADD(acc[1][i], acc[3][i], 0.5f);
        UPD_ADD(acc[3][i], acc[1][i], 2.0f / 15.0f);
      }
      done();
      tiles = __ballot_sync(0xffffffffu, tiles);
      if (tiles) {
        mbar_wait(bars + B_RD * 8);
        tiles = __shfl_sync(0xffffffffu, lds32(bars + O_TIL), 0);
        if (tiles < 0x10000u) correct<4>(acc, bars, tiles >> (wg * 4), code, lane);
      }
      corr(1, A);
      const uint32_t stg = sbase + warp * 1024, stb = bars + (B_ST + wg * 4) * 8;
      const uint32_t sa = stg + (lane & 15) * 64 + (((lane >> 4) ^ ((lane >> 1) & 3)) << 4);
      auto put = [&](const uint32_t* r, int i, int jp) {
        asm volatile("stmatrix.sync.aligned.m8n8.x4.shared.b16 [%0], {%1, %2, %3, %4};\n" ::"r"(
                         ((sa + guard + w_stg(wg, i)) ^ ((jp & 1) * 32)) + (jp >> 1) * 4096),
                     "r"(r[jp * 4]), "r"(r[jp * 4 + 1]), "r"(r[jp * 4 + 2]), "r"(r[jp * 4 + 3]) : "memory");
      };
      if (wg) mbar_wait(bars + (B_WE + 9) * 8);
      mbar_wait(bars + (B_WF + 12) * 8);
      uint32_t pk[2][24];
#pragma unroll
      for (int h = 0; h < 2; h++) {
        acc_fence(acc[2 - h]);
#pragma unroll
        for (int i = 0; i < 24; i++) pk[h][i] = pack2(acc[2 - h][i * 2] * (8.0f / 15.0f), acc[2 - h][i * 2 + 1] * (8.0f / 15.0f));
        guard = clock32() & never;
        if (h) publish(stb + 16, lane);
        if (!h || !LATE1) {
#pragma unroll
          for (int j = 0; j < 6; j++) put(pk[h], 2 - h, j);
        }
        done();
        corr(h * 3, A);
      }
      TSS(wg, 19);
      stage(acc[0], 12, w_slot(12), 10, 1, [&](int j) {
        if (LATE1) put(pk[1], 1, j);
        else if (j == P1J) publish(stb + 8, lane);
      }, false, false);
      stage(acc[0], 13, w_slot(13), 8, 1, [&](int j) {
        if (j == 1) keep_alive4(A, nv);
        if (j == 1 && LATE1) publish(stb + 8, lane);
      });
      stage(acc[0], 14, w_slot(14), 12, 1, [](int) {});
      auto row0 = [&](int n) {
        if (n == O1J) {
          mbar_wait(bars + (wg ? B_WL : B_SR) * 8);
          acc_fence(acc[0]);
#pragma unroll
          for (int i = 0; i < 24; i++) pk[0][i] = pack2(acc[0][i * 2], acc[0][i * 2 + 1]);
        }
        if (n >= O1J && n < O1J + 6 / OPER) {
#pragma unroll
          for (int k = 0; k < OPER; k++) put(pk[0], 0, (n - O1J) * OPER + k);
        }
        if (n == O1J + 6 / OPER + 1) publish(stb, lane);
      };
      stage(acc[3], 15, w_slot(15), 11, 1, [&](int j) { row0(j); });
      stage(acc[3], 16, w_slot(16), 9, 1, [&](int j) { row0(6 + j); }, !LEAN);
      stage(acc[3], 17, w_slot(17), 13, 1, [&](int j) { row0(12 + j); }, !LEAN);
      if (!wg) mbar_wait(bars + (B_SR + 1) * 8);
      wgmma_wait<0>();
      acc_fence(acc[3]);
      TSS(wg, 20);
      stage_slab(acc[3], stg + w_stg(wg, 3), lane);
      publish(stb + 24, lane);
      TSS(wg, 21);
      if (tiles >= 0x10000u) {
        ntiles = 4;
        tile0 = (x0 >> 3) + wg + (y0 << 5);
        tstep = 0x100;
      }
    } else if (strip) {
      const uint32_t tab = sbase + SM_GT + wid * 1152;
      TSS(wg, 28);
      {
        const int r = (warp & 1) * 4 + (lane & 3), c = lane >> 2, pu = wid * 4 + (lane & 3), pv = x0 + c;
        const uint32_t oa = sbase + SM_GO + (wid >> 1) * 2304 + (left ? c * 8 + r : r * 8 + c) * 36, swap = left ? 0x3210u : 0x1032u;
        uint32_t bad = 0;
        mbar_wait(bars + B_OG * 8);
        TSS(wg, 29);
#pragma unroll 1
        for (int tv = 0; tv < 3; tv++) {
          const uint32_t base = pack2((float)(pv + tv - 1), (float)pu);
#pragma unroll
          for (int tu = 0; tu < 3; tu++) {
            const int tap = left ? tv * 3 + tu : tu * 3 + tv;
            const uint32_t gp = hadd2(base, tap_delta(1, tu));
            uint32_t d = hsub2(clip2(hadd2(gp, prmt(lds32(oa + tap * 4), 0, swap))), clip2(gp));
            const bool out = tu == 0 && pu == 0, off = strip_off(d, out);
            bad |= off ? 1u << tap : 0u;
            d = out ? 0x3f800000u : off ? 0u : d & 0xffff0000u;
            sts32(tab + tv * 384 + tu * 128 + lane * 4, d | ((int)d < 0 ? 0x7654u : 0x3210u));
          }
        }
        if (bad && pv >= 34) push_taps(bars, strip_key(pu, pv, left), bad, offs);
        __syncwarp();
        arrive_if(lane == 0 ? bars + B_SG * 8 : 0u);
      }
#pragma unroll
      for (int i = 0; i < 48; i++) acc[0][i] = acc[1][i] = 0.0f;
      uint32_t la[3];
#pragma unroll
      for (int tv = 0; tv < 3; tv++) {
        const int p = (warp * 4 + ((lane >> 3) & 1)) * 10 + min((lane & 7) + tv, IW - x0);
        la[tv] = sbase + wg * GWIN + p * 64 + ((((lane >> 4) ^ (p >> 1)) & 3) << 4);
      }
      uint32_t D[2][8][2], A[3][8], dl[3][4];
#pragma unroll
      for (int i = 0; i < 24; i++) A[0][i] = nv;
#pragma unroll
      for (int tu = 0; tu < 3; tu++) lds128(dl[tu], tab + tu * 128 + (lane >> 2) * 16);
      auto fetch = [&](int b, uint32_t a) {
#pragma unroll
        for (int i = 0; i < 4; i++) ldsm4(D[b][2 * i][0], D[b][2 * i + 1][0], D[b][2 * i][1], D[b][2 * i + 1][1], (a ^ (((i + b) & 1) * 32)) + i * 2 * GROW);
      };
      TSS(wg, 23);
      mbar_wait(bars + (B_XF + wg * 3) * 8);
      fetch(0, la[0]);
      TSS(wg, 24);
      int tn = 1;
#pragma unroll 1
      for (int st = 0; st < 9; st++) {
        const uint64_t bd = w_desc(SB + SM_GW) + (st < 7 ? st : st - 7) * (STAGE >> 4);
        mbar_wait(bars + (B_XF + wg * 3 + (st >= 5 ? 2 : st >= 2)) * 8);
        mbar_wait(bars + (B_WF + st) * 8);
        TSS(wg, st);
#pragma unroll
        for (int kh = 0; kh < 2; kh++) {
          fetch(kh ^ 1, la[kh]);
          uint32_t E[7][2];
#pragma unroll
          for (int tu = 0; tu < 3; tu++) {
            wgmma_wait<2>();
            keep_alive8(A[tu], nv);
            if (kh == 1 && tu == 0) arrive_if((st == 1 || st == 2) && lane < 2 ? we_addr + st * 8 - 8 : 0u);
#pragma unroll
            for (int i = 0; i < 8; i++) {
              const int r = (i >> 2) * 2 + (i & 1), h = (i >> 1) & 1;
              if (tu == 0 && r == 0) E[0][h] = hsub2(D[kh][1][h], D[kh][0][h]);
              if (tu == 0 || r == 3) E[r + tu + 1][h] = hsub2(D[kh][r + tu + 2][h], D[kh][r + tu + 1][h]);
              A[tu][i] = hfma2_h(dl[tu][r], 1, prmt(E[r + tu + 1][h], E[r + tu][h], dl[tu][r]), D[kh][r + tu + 1][h]);
              if ((i & 3) == 3) {
                wgmma_fence();
                wgmma_rs(acc[i >> 2], A[tu] + (i & 4), bd + tu * WTAP + kh * WHALF);
              }
            }
            wgmma_commit();
            if (kh) lds128(dl[tu], tab + tn * 384 + tu * 128 + (lane >> 2) * 16);
          }
        }
        const uint32_t l0 = la[0] + (st < 6 ? GSLICE : 0);
        la[0] = la[1];
        la[1] = la[2];
        la[2] = l0;
        tn = tn == 2 ? 0 : tn + 1;
      }
      mbar_wait(bars + B_RD * 8);
      const uint32_t tiles = __shfl_sync(0xffffffffu, lds32(bars + O_TIL), 0);
      wgmma_wait<0>();
#pragma unroll
      for (int i = 0; i < 3; i++) keep_alive8(A[i], nv);
      if (tiles < 0x10000u) {
        correct<2>(acc, bars, tiles >> (wg * 4), (wg * 512 + warp * 32 + (lane >> 2) + 0x4000u) * 0x10001u, lane);
      } else {
        ntiles = 2;
        tile0 = left ? wg * 2 + (x0 << 5) : (x0 >> 3) + (wg << 9);
        tstep = left ? 1 : 0x100;
      }
      acc_fence(acc[0]);
      acc_fence(acc[1]);
      TSS(wg, 20);
      bar_sync(1 + wg, 128);
      const uint32_t stg = sbase + wg * GWIN + warp * 2048;
      stage_slab<8192>(acc[0], stg, lane);
      stage_slab<8192>(acc[1], stg + 1024, lane);
      publish(bars + (B_ST + wg * 4) * 8, lane);
      TSS(wg, 21);
    } else {
      ntiles = !wg || cta >= -4;
      tile0 = corner_tile(wg);
      if (!ntiles) {
        const int src = cta + NC, t = tid & 127;
        arrive_if(lane == 0 ? bars + B_SG * 8 : 0u);
        const uint32_t tag = scr->launch[blockIdx.x] + 1;
        const int lf = src == 0 || src == 7 ? t < 64 : src >= 4;
        const int along = ((0x0c84b842u >> (4 * src)) & 15) * 16 + (src == 0 || src == 7 ? (t >> 1) & 31 : t >> 1);
        const int oy = lf ? along : 32 + (t & 1), ox = lf ? 32 + (t & 1) : along;
        if (src == 0 ? !lf || along >= 34 : along < (src == 2 ? 176 : 224)) {
          const uint32_t key = src < 7 ? wino_key(oy, ox) : strip_key(along, 32 + (t & 1), !lf);
          uint32_t o2[9];
          TSS(wg, 3);
#pragma unroll
          for (int m = 0; m < 9; m++) o2[m] = __ldg(offs + (oy * IW + ox) * 9 + m);
          TSS(wg, 4);
          const uint32_t base = pack2((float)oy, (float)ox), swap = lf ? 0x1032u : 0x3210u, outs = along ? 0u : lf ? 7u : 0x49u;
          uint32_t bad = 0;
#pragma unroll
          for (int m = 0; m < 9; m++) {
            const uint32_t gp = hadd2(base, tap_delta(m / 3, m % 3));
            bad |= strip_off(prmt(hsub2(clip2(hadd2(gp, o2[m])), clip2(gp)), 0, swap), src < 7 || ((outs >> m) & 1)) ? 1u << m : 0u;
          }
          if (bad) push_taps(bars, key, bad, offs);
        }
        bar_sync(2, 128);
        TSS(wg, 0);
        const int n = __shfl_sync(0xffffffffu, lds32(bars + O_CNT), 0);
        if (n && n <= NREC) {
          const uint32_t tmp = sbase + SM_CX + CWIN;
#pragma unroll 1
          for (int i = t; i < n * 12; i += 128) {
            const int r = (i * 171) >> 11;
            uint32_t key, pos, v[4];
            lds64(key, pos, bars + O_REC + r * 8);
            delta(v, key, pos, reinterpret_cast<const uint4*>(x), i - r * 12);
            sts128(tmp + (r + i) * 16, v);
          }
          bar_sync(2, 128);
          TSS(wg, 5);
          const int r0 = warp ? 99 : lane >> 2;
          const uint32_t k0 = lds32(bars + O_REC + (lane >> 2) * 8), k1 = lds32(bars + O_REC + 64 + (lane >> 2) * 8);
          const uint32_t t0 = r0 < n ? (k0 >> 16) & 15 : 15, t1 = r0 + 8 < n ? (k1 >> 16) & 15 : 15;
          const uint32_t taps = __reduce_or_sync(0xffffffffu, lane < n ? 1u << ((lds32(bars + O_REC + (lane & 15) * 8) >> 16) & 15) : 0u);
          uint32_t D[6][4];
#pragma unroll
          for (int k = 0; k < 6; k++) ldsm4(D[k], tmp + (lane & 15) * 208 + (lane >> 4) * 16 + k * 32);
#pragma unroll
          for (int i = 0; i < 48; i++) acc[0][i] = 0.0f;
#pragma unroll 1
          for (int st = 0; st < 9; st++) mbar_wait(bars + (B_WF + st) * 8);
#pragma unroll 1
          for (uint32_t m = taps; m; m &= m - 1) {
            const uint32_t tap = __ffs(m) - 1, ki = (tap * 11) >> 5;
            uint32_t A[6][4];
#pragma unroll
            for (int k = 0; k < 6; k++) {
#pragma unroll
              for (int i = 0; i < 4; i++) A[k][i] = (i & 1 ? t1 : t0) == tap ? D[k][i] : 0u;
            }
            wgmma_fence();
#pragma unroll
            for (int k = 0; k < 6; k++)
              wgmma_rs(acc[0], A[k], w_desc(SB) + ((k >> 1) * 3 + ki) * (STAGE >> 4) + (tap - ki * 3) * WTAP + (k & 1) * WHALF);
            wgmma_commit();
            wgmma_wait<0>();
#pragma unroll
            for (int k = 0; k < 3; k++) keep_alive8(A[2 * k], nv);
          }
          acc_fence(acc[0]);
          TSS(wg, 6);
          if (!warp) {
            uint32_t* dst = reinterpret_cast<uint32_t*>(scr->fix) + src * 768 + (lane >> 2) * 16 + (lane & 3);
#pragma unroll
            for (int j = 0; j < 24; j++) dst[(j >> 3) * 256 + (j & 1) * 128 + ((((j >> 1) ^ (lane >> 3)) & 3) << 2)] = pack2(acc[0][j * 2], acc[0][j * 2 + 1]);
          }
        }
        TSS(wg, 1);
        if (!warp) {
          __threadfence();
          __syncwarp();
          if (lane < NREC)
            asm volatile("st.relaxed.gpu.global.v2.u32 [%0], {%1, %2};\n" ::"l"(scr->key + src * NREC + lane), "r"(lds32(bars + O_REC + lane * 8)),
                         "r"((tag << 8) | min(n, 99)) : "memory");
          if (lane == 0) scr->launch[blockIdx.x] = tag;
        }
        TSS(wg, 2);
      }
    }
    if (ntiles) {
      const uint32_t winb = sbase + SM_CX + wg * CWIN, tab = sbase + SM_CT + wid * 1152;
      const uint32_t ck = (uint32_t)(lane >> 4) << 4, again = tstep != 0;
      if (tstep) {
        bar_sync(3, 256);
        if (wid == 0 && one) {
#pragma unroll 1
          for (int st = 0; st < 9; st++) load_cw(st);
        }
        __syncwarp();
      }
#pragma unroll 1
      for (int n = 0; n < ntiles; n++) {
        const uint32_t tl = tile0 + n * tstep;
        const int wx0 = (int)(tl & 255) * 8 - 2, wy0 = (int)(tl >> 8) * 8 - 2;
        if (tstep && warp == 0 && one) {
#pragma unroll 1
          for (int g = 0; g < 3; g++) load_cx(wg, g, tl);
        }
        __syncwarp();
        TSS(wg, 28);
        uint32_t mout = 0, need = 0, of[5];
        {
          const int ph = wy0 + 2 + 2 * warp + ((lane >> 3) & 1), pw = wx0 + 2 + (lane & 7);
          if (tstep) {
#pragma unroll
            for (int k = 0; k < 5; k++) of[k] = __ldg(offs + (ph * IW + pw) * 9 + min((lane >> 4) + 2 * k, 8));
          } else {
            mbar_wait(bars + B_OG * 8);
#pragma unroll
            for (int k = 0; k < 5; k++) of[k] = lds32(winb + 2 * CSLICE + (warp * 16 + (lane & 15)) * 36 + min((lane >> 4) + 2 * k, 8) * 4);
          }
#pragma unroll 1
          for (int m = lane >> 4; m < 9; m += 2) {
            const int ki = (m * 11) >> 5;
            const uint32_t pos = clip2(hadd2(pack2((float)(ph + ki - 1), (float)(pw + m - ki * 3 - 1)), of[0]));
#pragma unroll
            for (int k = 0; k < 4; k++) of[k] = of[k + 1];
            const uint32_t iy = (int)bf16lo(pos) - wy0, ix = (int)bf16hi(pos) - wx0, f = frac2(pos);
            mout |= max(iy, ix) > 10 ? 1u << m : 0u;
            need |= ((f >> 16 ? 1u : 0u) | (f & 0xffffu ? 0x200u : 0u) | (f >> 16 && f & 0xffffu ? 0x40000u : 0u)) << m;
            const uint32_t pp = (iy * 12 + ix) * 0x10001u + 0x10000u;
            sts32(tab + m * 64 + (lane & 7) * 8 + ((lane >> 1) & 4), f);
            sts32(tab + 576 + m * 64 + (lane & 15) * 4, pp * 64 + ((pp << 3) & 0x300030u));
            of[4] = pos;
          }
          mout = __reduce_or_sync(0xffffffffu, mout);
          need = __reduce_or_sync(0xffffffffu, need);
          arrive_if(lane == 0 && !tstep ? bars + B_SG * 8 : 0u);
        }
        TSS(wg, 29);
        uint32_t outside;
        asm volatile("{\n.reg .pred p, q;\nsetp.ne.u32 p, %1, 0;\nbarrier.red.or.pred q, %2, 128, p;\nselp.u32 %0, 1, 0, q;\n}\n"
                     : "=r"(outside) : "r"(mout), "r"(1 + wg) : "memory");
        outside = __shfl_sync(0xffffffffu, outside, 0);
#pragma unroll
        for (int i = 0; i < 48; i++) acc[0][i] = 0.0f;
        if (!outside) {
          uint32_t T[3][4], C[2][3][4];
#pragma unroll
          for (int i = 0; i < 12; i++) T[0][i] = C[0][0][i] = C[1][0][i] = nv;
          uint32_t ad[4];
          auto fetch = [&](int k, uint32_t e, uint32_t slice, uint32_t nd) {
            if (!(k & 1)) {
              ad[0] = (e & 0xffffu) + slice;
              ad[1] = (e >> 16) + slice;
              ad[2] = ad[0] ^ 32;
              ad[3] = ad[1] ^ 32;
            }
            ldsm4_if(T[k % 3], ad[(k & 1) * 2], never ^ 1);
            ldsm4_if(C[k & 1][0], ad[(k & 1) * 2 + 1], nd & 1);
            ldsm4_if(C[k & 1][1], ad[2 - (k & 1) * 2] + CROW, nd & 0x200u);
            ldsm4_if(C[k & 1][2], ad[3 - (k & 1) * 2] + CROW, nd & 0x40000u);
          };
          uint32_t ent[3], slice = winb;
          const uint32_t ck2 = ck * 0x10001u;
          mbar_wait(bars + (B_XF + wg * 3) * 8, (n + again) & 1);
          fetch(0, lds32(tab + 576 + (lane & 15) * 4) ^ ck2, slice, need);
          int ki = 0, g = 0;
#pragma unroll 1
          for (int st = 0; st < 9; st++) {
            const uint64_t bd = w_desc(SB) + st * (STAGE >> 4);
            const int kn = ki == 2 ? 0 : ki + 1;
            uint32_t cf[3][4];
#pragma unroll
            for (int j = 0; j < 3; j++) {
              uint32_t wA, wB;
              lds64(wA, wB, tab + (ki * 3 + j) * 64 + (lane >> 2) * 8);
              ent[j] = lds32(tab + 576 + (j < 2 ? ki * 3 + j + 1 : kn * 3) * 64 + (lane & 15) * 4) ^ ck2;
              coefs(wA, cf[j][0], cf[j][1]);
              coefs(wB, cf[j][2], cf[j][3]);
            }
            if (kn == 0 && g < 2) mbar_wait(bars + (B_XF + wg * 3 + g + 1) * 8, (n + again) & 1);
            mbar_wait(bars + (B_WF + st) * 8, again);
            TSS(wg, st);
#pragma unroll
            for (int k = 0; k < 6; k++) {
              wgmma_wait<1>();
              if (k == 5 && kn == 0 && g < 2) {
                g++;
                slice += CSLICE;
              }
              fetch(k + 1, ent[k >> 1], slice, need >> (k < 5 ? ki * 3 + ((k + 1) >> 1) : kn * 3));
              blend4(T[k % 3], C[k & 1][0], C[k & 1][1], C[k & 1][2], cf[k >> 1][0], cf[k >> 1][1], cf[k >> 1][2], cf[k >> 1][3]);
              wgmma_fence();
              wgmma_rs(acc[0], T[k % 3], bd + (k >> 1) * WTAP + (k & 1) * WHALF);
              wgmma_commit();
            }
            ki = kn;
          }
          wgmma_wait<0>();
          keep_alive8(T[0], nv);
          keep_alive8(T[1], nv);
        } else {
#pragma unroll
        for (int k = 0; k < 5; k++) {
          const int m = 2 * k - (lane >> 4);
          if (m >= 0) sts32(tab + m * 64 + (lane & 7) * 8 + ((lane >> 1) & 4), of[k]);
        }
        __syncwarp();
        uint32_t buf[2][8];
#pragma unroll
        for (int i = 0; i < 16; i++) buf[0][i] = nv;
        const uint32_t tmp = tab + 576 + lane * 16;
        int tap = 0, g = 0;
#pragma unroll 1
        for (int d = 0;; d += 2) {
#pragma unroll
          for (int b = 0; b < 2; b++) {
            const int k = d + b, q = (k * 11) >> 5;
            if (k == 27) goto tile_done;
            mbar_wait(bars + (B_XF + wg * 3 + g) * 8, (n + again) & 1);
            mbar_wait(bars + (B_WF + q) * 8, again);
            if (k == q * 3) TSS(wg, q);
            const uint32_t pos = lds32(tab + tap * 64 + (lane & 7) * 8 + ((lane >> 1) & 4));
            const int gy = (int)bf16lo(pos), gx = (int)bf16hi(pos);
            uint32_t T[8];
            if (!((mout >> tap) & 1)) {
              uint32_t wA, wB, pA0, pA1, pB0, pB1, G[4], H[4], K[4];
              lds64(wA, wB, tab + tap * 64 + (lane >> 2) * 8);
              const uint32_t slice = winb + g * CSLICE;
              const uint32_t p = (gy - wy0) * 12 + gx - wx0, p1 = p + 1;
              const uint32_t a00 = slice + p * 64 + (((p << 3) & 0x30) ^ ck), a01 = slice + p1 * 64 + (((p1 << 3) & 0x30) ^ ck);
              coefs(frac2(wA), pA0, pA1);
              coefs(frac2(wB), pB0, pB1);
#pragma unroll
              for (int hf = 0; hf < 2; hf++) {
                ldsm4(T + hf * 4, a00 ^ (hf * 32));
                ldsm4(G, a01 ^ (hf * 32));
                ldsm4(H, (a00 + CROW) ^ (hf * 32) ^ 32);
                ldsm4(K, (a01 + CROW) ^ (hf * 32) ^ 32);
                blend4(T + hf * 4, G, H, K, pA0, pA1, pB0, pB1);
              }
            } else {
              uint32_t q0, q1;
              coefs(frac2(pos), q0, q1);
              const int sx = gx < IW - 1 ? IC / 8 : 0, sy = gy < IH - 1 ? IW * IC / 8 : 0;
              const uint4* pc = reinterpret_cast<const uint4*>(x) + (gy * IW + gx) * (IC / 8) + g * 4 + (lane >> 4);
#pragma unroll
              for (int hf = 0; hf < 2; hf++) {
                uint4 v[4];
                v[0] = __ldg(pc + hf * 2);
                v[1] = __ldg(pc + hf * 2 + sx);
                v[2] = __ldg(pc + hf * 2 + sy);
                v[3] = __ldg(pc + hf * 2 + sy + sx);
                blend4(&v[0].x, &v[1].x, &v[2].x, &v[3].x, q0, q1, q0, q1);
                __syncwarp();
                sts128(tmp, &v[0].x);
                __syncwarp();
                ldsm4(T + hf * 4, tmp);
              }
            }
            wgmma_wait<1>();
            keep_alive8(buf[b], nv);
#pragma unroll
            for (int i = 0; i < 8; i++) asm volatile("xor.b32 %0, %1, %2;\n" : "=r"(buf[b][i]) : "r"(T[i]), "r"(nv));
            const uint64_t bd = w_desc(SB) + q * (STAGE >> 4) + (k - q * 3) * WTAP;
            wgmma_fence();
            wgmma_rs(acc[0], buf[b], bd);
            wgmma_rs(acc[0], buf[b] + 4, bd + WHALF);
            wgmma_commit();
            if (++tap == 9) {
              tap = 0;
              g++;
            }
          }
        }
      tile_done:
        wgmma_wait<0>();
        keep_alive8(buf[0], nv);
        keep_alive8(buf[1], nv);
        }
        acc_fence(acc[0]);
        TSS(wg, 20);
        bar_sync(1 + wg, 128);
        stage_slab(acc[0], winb + warp * 1024, lane);
        fence_async();
        bar_sync(1 + wg, 128);
        if (warp == 0 && one) {
          tma_store(&tm.out[3], winb, wx0 + 2, wy0 + 2, 0);
          asm volatile("cp.async.bulk.wait_group.read 0;\n" ::: "memory");
        }
        TSS(wg, 21);
      }
    }
    if (warp == 0) TSDUMP(wg);
  } else if (wid < 12) {
    asm volatile("setmaxnreg.dec.sync.aligned.u32 40;\n");
    if (prep) {
      const int lane = lane_now();
      uint32_t u[4][4];
      weights4(&g[0].x, &g[1].x, &g[2].x, u);
      const uint8_t* udst = scr->u + ((cta >> 2) & 1) * (4 * STAGE) + (cta & 2) * (STAGE / 4) + ((cta - NW) >> 3) * 3072 + (wid - 8) * 1024 +
                            (cta & 1) * 512 + (lane >> 2) * 64 + (((lane ^ (lane >> 3)) & 3) << 4);
#pragma unroll
      for (int k = 0; k < 4; k++)
        asm volatile("st.relaxed.gpu.global.v4.b32 [%0], {%1, %2, %3, %4};\n" ::"l"(udst + k * STAGE), "r"(u[k][0]), "r"(u[k][1]), "r"(u[k][2]), "r"(u[k][3]) : "memory");
      uint32_t chk = 0;
#pragma unroll
      for (int k = 0; k < 4; k++) {
        uint32_t v;
        asm volatile("ld.relaxed.gpu.global.b32 %0, [%1];\n" : "=r"(v) : "l"(udst + k * STAGE) : "memory");
        chk |= v;
      }
      chk = __reduce_or_sync(0xffffffffu, chk & never);
      if (one) asm volatile("red.relaxed.gpu.global.add.u32 [%0], %1;\n" ::"l"(scr->cnt), "r"(chk + 1) : "memory");
      TS(5, 21);
    }
    asm volatile("barrier.cluster.wait.acquire.aligned;\n" ::: "memory");
    const int w = wid - 8, lane = lane_now();
    if (wino) {
      bar_sync(12, 384);
      arrive_if(one ? bars + (B_WF + w) * 8 : 0u);
      const int hi = w >> 1, ty = (w & 1) * 4 + (lane >> 4);
      const bool bottom = y0 + 4 * ty + 12 == IH;
      uint32_t d[2][6][2];
      auto fetch = [&](int u, uint32_t src, bool low = false) {
#pragma unroll
        for (int r = 0; r < 5; r++) lds64(d[u][r][0], d[u][r][1], src + u * 1024 + r * 128);
        lds64(d[u][5][0], d[u][5][1], src + u * 1024 + ((u || low) && bottom ? 4 * 128 : 5 * 128));
      };
      uint32_t src = sbase + SM_R + hi * PIECE + ty * 512 + (lane & 15) * 8;
      uint32_t v0 = sbase + ty * VROW + hi * 128 + (lane & 8) * 8 + (lane & 1) * 8 + ((((lane >> 1) ^ (ty + hi)) & 3) << 4);
      auto vl = [&] { return (v0 ^ (hi ? (lane_now() & 16 ? 16 : 48) : 0)) + 1024 + hi * (2 * VROW - 128); };
      mbar_wait(bars + (B_XF + 2) * 8);
      fetch(0, src + 4 * VSLOT - SM_R + (4 - hi) * PIECE + hi * 1024, hi);
      transform6<2>(d[0], vl() - 512, 10 * VSLOT);
      publish(bars + B_V0 * 8, !one);
      mbar_wait(bars + B_V0 * 8);
      mbar_wait(bars + (B_VF + 1) * 8);
      v0 += 4 * VSLOT;
#pragma unroll 1
      for (int s = 0; s < 2; s++) {
        const uint32_t xf = bars + (B_XF + 5 + s * 5) * 8, off0 = s ? 12 * VSLOT : 4 * VSLOT;
        if (!TB || !s) {
          if (s) mbar_wait(bars + B_VE * 8);
          mbar_wait(xf);
          fetch(0, src);
        }
#pragma unroll 1
        for (int jj = 0; jj < 4; jj += 2) {
          asm volatile("" : "+r"(src), "+r"(v0));
#pragma unroll
          for (int e = 0; e < 2; e++) {
            const int j = jj + e;
            if (w == 0) TS(7, 5 + s * 5 + j);
            const uint32_t ready = mbar_poll(xf + j * 8 + 8);
            fetch(1, src + e * 2 * PIECE);
            transform6<2>(d[0], (v0 ^ e * 32) + e * 256, off0);
            if (!ready) mbar_wait(xf + j * 8 + 8);
            fetch(0, (src + ((e + 1) * 2 * PIECE - (j == 3 ? hi * (PIECE - 1024) : 0))) & (j == 3 && x0 + 16 == IW ? ~64u : ~0u), j == 3 && hi);
            transform6<2>(d[1], (v0 ^ (e ^ 1) * 32) + e * 256 + 2 * VROW, off0);
            __syncwarp();
            arrive_if(one && (!s || j == 2) ? bars + (B_RE + j + s * 3) * 8 : 0u);
            if (j + hi == 2) publish(bars + (B_VF + 2 + s * 2) * 8, !one);
          }
          src += 4 * PIECE;
          v0 += 512;
        }
        if (w == 0) TS(7, 9 + s * 5);
        const uint32_t ready = TB && !s ? mbar_poll(xf + 40) & mbar_poll(bars + B_VE * 8) : 0;
        transform6<2>(d[0], vl() - 1024, off0);
        if (TB && ready) fetch(0, src - 8 * PIECE);
        publish(bars + (B_VF + 3 + s * 2) * 8, !one);
        if (TB && !s && !ready) {
          mbar_wait(bars + B_VE * 8);
          mbar_wait(xf + 40);
          fetch(0, src - 8 * PIECE);
        }
        arrive_if(one && !s ? bars + (B_RE + 4) * 8 : 0u);
        v0 -= 4 * VSLOT + 1024;
        src -= 8 * PIECE;
      }
      if (w == 0) TS(7, 15);
        {
          mbar_wait(bars + B_OF * 8);
          if (w == 0) TS(7, 16);
          const uint32_t ob = sbase + SM_R + w * 4608;
          uint32_t mx = 0;
#pragma unroll
          for (int h = 0; h < 2; h++) {
            uint32_t v[5][4];
#pragma unroll
            for (int k = 0; k < 5 - h; k++) lds128(v[k], ob + (h * 5 + k) * 512 + lane * 16);
#pragma unroll
            for (int k = 0; k < 5 - h; k++)
              mx = absmax2(mx, absmax2(absmax2(v[k][0], v[k][1]), absmax2(v[k][2], v[k][3])));
          }
          const uint32_t lim = (pack2((float)max(y0, 34) - 1.5f, (float)max(x0, 34) - 1.5f) & 0x7f807f80u) - 0x04000400u;
          uint32_t who = __ballot_sync(0xffffffffu, (mx & 0x7fffu) >= (lim & 0xffffu) || (mx & 0x7fff0000u) >= (lim & 0xffff0000u));
#pragma unroll 1
          for (; who; who &= who - 1) {
#pragma unroll 1
            for (int k = lane; k < 64; k += 32) {
              const int wd = (k >> 2) * 128 + (__ffs(who) - 1) * 4 + (k & 3), c = (wd * 7282) >> 16, tap = wd - c * 9, ki = (tap * 11) >> 5;
              const int y = y0 + w * 8 + (c >> 4), xx = x0 + (c & 15);
              if (k < 36 && min(y, xx) >= 34) {
                const uint32_t gp = pack2((float)(y + ki - 1), (float)(xx + tap - ki * 3 - 1));
                const uint32_t pos = clip2(hadd2(gp, lds32(ob + wd * 4)));
                if (pos != clip2(gp)) push_record(bars, wino_key(y, xx) | (tap << 16), pos);
              }
              __syncwarp();
            }
          }
          bar_sync(8 + w, 32);
          arrive_if(one ? bars + B_SW * 8 : 0u);
        }
      if (w == 0) TS(7, 17);
    }
    if (wino || strip) {
      mbar_wait(bars + (wino ? B_SW : B_SG) * 8);
      mbar_wait(bars + B_IM * 8);
      uint32_t n0, tiles;
      lds64(n0, tiles, bars + O_CNT);
      n0 = __shfl_sync(0xffffffffu, n0, 0);
      if (n0 > NREC) {
        tiles = 0x10000u;
      } else if (n0) {
        fixup(bars, w, n0, reinterpret_cast<const uint4*>(x), wgt);
        const int lane = lane_now();
        tiles = lds32(bars + O_CNT + 4);
        const uint32_t key = lane < n0 ? lds32(bars + O_REC + lane * 8) : ~0u;
        put_sel(bars + 32, key, lane);
        tiles |= __reduce_or_sync(0xffffffffu, lane < n0 ? 256u << (key >> 27) : 0u);
        fence_async();
        bar_sync(4, 128);
      }
      if (w == 0 && one) {
        sts32(bars + O_TIL, wino ? tiles & ~255u : tiles);
        arrive_if(bars + B_RD * 8);
        atomicAdd(scr->launch + blockIdx.x, 1);
        if (wino) atomicInc(scr->cnt, 72 + NW - 1);
      }
      if (w == 0) TS(7, 21);
      if (w == 0) TSDUMP(7);
    }
  } else {
    if (wid == 15) TS(6, 23);
    asm volatile("setmaxnreg.dec.sync.aligned.u32 24;\n");
    asm volatile("barrier.cluster.wait.acquire.aligned;\n" ::: "memory");
    auto wait_all = [&](uint32_t dt) {
      while (__shfl_sync(0xffffffffu, clock32(), 0) - tstart < dt) __nanosleep(40);
    };
    if (wid == 15 && !wino) {
      const uint32_t dst = sbase + (strip ? SM_GW : 0) + (cta & 1) * (STAGE / 2);
      int g = 0, r = 0;
#pragma unroll 1
      for (int k = 0; k < 9; k++) {
        if (strip && k >= 7) mbar_wait(bars + (B_WE + k - 7) * 8);
        else wait_all(strip ? GW0 + k * GWS : CW0 + k * CWS);
        if (one) {
          mbar_expect_tx(bars + (B_WF + k) * 8, STAGE);
          tma_load_w(dst + (strip && k >= 7 ? k - 7 : k) * STAGE, &tm.w[left], bars + (B_WF + k) * 8, g + (cta & 1) * 16, left ? 0 : r, left ? r : 0, 3);
        }
        TS1(6, k);
        if (++r == 3) {
          r = 0;
          g += 32;
        }
      }
    }
    if (wid >= 13 && wid < 15 && !wino) {
      const int r = 14 - wid;
      const uint32_t tl = corner_tile(r);
#pragma unroll 1
      for (int g = 0; g < 3; g++) {
        if (g == 2) mbar_wait(bars + B_SG * 8);
        wait_all(strip ? (r ? GX1 + g * GXS1 : GX0 + g * GXS) : CX0 + g * CXS);
        if (one && (strip ? g || r >= GTOP : !r || cta >= -4))
          tma_load_x(sbase + (strip ? r * GWIN + g * GSLICE : SM_CX + r * CWIN + g * CSLICE), &tm.x[strip ? 1 + left : 3],
                     bars + (B_XF + r * 3 + g) * 8, strip ? GSLICE : CSLICE, g * 32, strip ? x0 - 1 : (int)(tl & 255) * 8 - 2,
                     strip ? r * 16 - 2 : (int)(tl >> 8) * 8 - 2);
      }
    }
    if (wid == 15 && wino) {
      if (one) {
        if (NA0 < 5) wait_until(tstart, BDELAY);
#pragma unroll
        for (int j = NA0; j < 5; j++) load_cols(0, j);
        wait_until(tstart, SDELAY);
#pragma unroll
        for (int j = 0; j < NS1; j++) load_cols(1, j);
        wait_until(tstart, SDELAY + SDELAY2);
#pragma unroll
        for (int j = NS1; j < 5; j++) load_cols(1, j);
        TS(5, 0);
        wait_until(tstart, PDELAY);
        TS1(6, 20);
              asm volatile(
                  "{\n.reg .pred p;\n.reg .u32 n, v;\nmov.u32 n, 0;\n"
                  "W_%=:\n"
                  "ld.relaxed.gpu.global.u32 v, [%0];\nsetp.ge.u32 p, v, 72;\n"
                  "@p bra D_%=;\n"
                  "add.u32 n, n, 1;\nsetp.lt.u32 p, n, 0x100000;\n@p bra W_%=;\ntrap;\n"
                  "D_%=:\n}\n" ::"l"(scr->cnt)
                  : "memory");
              asm volatile("fence.proxy.async.global;\n" ::: "memory");
        TS1(6, 21);
      }
      bar_sync(13, 32);
    }
    if (wid == 15) TS(6, 24);
    if (wid == 15) {
      if (wino) {
#pragma unroll 1
        for (int k = 0; k < 8; k++) {
          mbar_wait(bars + (B_WE + ((0x77654210u >> (4 * k)) & 15)) * 8);
          if (one)
            bulk_load_mc(sbase + (uint32_t)((w_slots(4, 1, 8) >> (8 * k)) & 255) * 1024 + (cta & 1) * (STAGE / 2),
                         scr->u + (k * 2 + (cta & 1)) * (STAGE / 2), STAGE / 2, bars + (B_WF + 4 + k) * 8);
          TS1(6, 4 + k);
        }
#pragma unroll
        for (int k = 0; k < 6; k++) {
          if (k > 0 && k < 5) mbar_wait(bars + (B_WE + min(7 + k, 11)) * 8);
          if (one)
            tma_load_w(sbase + (uint32_t)((w_slots(12, 1, 6) >> (8 * k)) & 255) * 1024 + (cta & 1) * (STAGE / 2), &tm.w[1],
                       bars + (B_WF + 12 + k) * 8, (k < 3 ? k : k - 3) * 32 + (cta & 1) * 16, 0, k < 3 ? 0 : 2, 3);
          TS1(6, 12 + k);
        }
      }
      TSDUMP(6);
    } else if (wid == 14) {
      if (one) {
        if (wino) {
#pragma unroll
          for (int j = 0; j < 5; j++) {
            mbar_wait(bars + (B_RE + j) * 8);
            load_cols(2, j);
            TS(5, 5 + j);
          }
        }
      }
      bar_sync(6, 32);
      if (wino || strip) {
        const int lane = lane_now();
        TS(5, 10);
        const uint32_t tag = scr->launch[blockIdx.x] + 1;
        uint32_t n = 0;
        if (x0 == 32 || (wino && y0 == 32)) {
          const int src = !wino ? 7 : ry ? (ry + 7) >> 1 : (0xfea550u >> (2 * cta)) & 3;
          uint32_t key, v;
          asm volatile(
              "{\n.reg .pred p;\n.reg .u32 n, t;\nmov.u32 n, 0;\n"
              "W_%=:\n"
              "ld.acquire.gpu.global.v2.u32 {%0, %1}, [%2];\nxor.b32 t, %1, %3;\nsetp.lt.u32 p, t, 256;\nvote.sync.all.pred p, p, 0xffffffff;\n"
              "@p bra D_%=;\n"
              "add.u32 n, n, 1;\nsetp.lt.u32 p, n, 0x100000;\n@p bra W_%=;\ntrap;\n"
              "D_%=:\nfence.proxy.async.global;\n}\n"
              : "=r"(key), "=r"(v)
              : "l"(scr->key + src * NREC + (lane & 15)), "r"(tag << 8)
              : "memory");
          v &= 255;
          const uint32_t dy = (key & 255) - (wino ? y0 : left ? 32 : 0), dx = ((key >> 8) & 255) - (wino || !left ? x0 : 0);
          const bool mine = lane < v && dy < 32 && dx < (left ? 32 : 16);
          n = __reduce_or_sync(0xffffffffu, v > NREC ? 0x10000u : mine ? 1u << (key >> 27) : 0u);
          put_sel(bars, mine ? key : ~0u, lane);
          if (n && n < 256 && one) {
            asm volatile("mbarrier.expect_tx.relaxed.cta.shared::cta.b64 [%0], 3072;\n" ::"r"(bars + B_IM * 8) : "memory");
            asm volatile("cp.async.bulk.shared::cluster.global.mbarrier::complete_tx::bytes [%0], [%1], 3072, [%2];\n" ::"r"(sbase + SM_FIX),
                         "l"(scr->fix + src * 192), "r"(bars + B_IM * 8) : "memory");
          }
          __syncwarp();
        }
        if (lane == 0) sts32(bars + O_CNT + 4, n + (tag & never));
        __syncwarp();
        arrive_if(lane == 0 ? bars + B_IM * 8 : 0u);
        TS(5, 11);
        TSDUMP(5);
      }
    } else if (wino || strip) {
      const int wg = wid - 12;
      if (one) {
        if (wino && wg) {
#pragma unroll 1
          for (int i = 4; i < 18; i++) mbar_expect_tx(bars + (B_WF + i) * 8, STAGE);
        } else if (wino) {
#pragma unroll 1
          for (int i = 0; i < 15; i++) mbar_expect_tx(bars + (B_XF + i) * 8, (0x4210 >> i) & 1 ? PIECE : 2 * PIECE);
        }
        asm volatile("prefetch.tensormap [%0];\n" ::"l"(reinterpret_cast<uint64_t>(&tm.out[wino ? wg * 4 : 1 + left])) : "memory");
      }
      if (wino && !wg) {
        if (one) {
          wait_until(tstart, FDELAY);
          asm volatile("cp.async.bulk.prefetch.tensor.2d.L2.global [%0, {%1, %2}];\n" ::"l"(reinterpret_cast<uint64_t>(&tm.o[0])), "r"(x0 * 9), "r"(y0) : "memory");
          mbar_expect_tx(bars + B_OF * 8, 2 * VSLOT);
          mbar_wait(bars + B_R2 * 8);
          tma_load_o(sbase + SM_R, &tm.o[0], bars + B_OF * 8, x0, y0);
        }
        bar_sync(7, 32);
      }
      mbar_wait(bars + B_RD * 8);
      if (__all_sync(0xffffffffu, lds32(bars + O_TIL) < 0x10000u)) {
        const CUtensorMap* map = &tm.out[wino ? 0 : 1 + left];
        const int c1 = x0 + (wino ? wg * 8 : 0), c3 = wino ? y0 >> 2 : 0;
        TS1(wid - 10, 19);
#pragma unroll 1
        for (int i = wino ? 2 : 0;; i = (i - 1) & 3) {
          const uint32_t stg = sbase + (wino ? w_stg(wg, i) : wg * GWIN), sb = bars + (B_ST + wg * 4 + i) * 8;
          mbar_wait(sb);
          if (one) tma_store(map, stg, c1, wino ? i : wg * 16, c3);
          TS1(wid - 10, 20 + ((2 - i) & 3));
          if (!wg && wino && i < 2) {
            asm volatile("cp.async.bulk.wait_group.read 1;\n" ::: "memory");
            arrive_if(one ? bars + (B_SR + 1 - i) * 8 : 0u);
          }
          if (i == (DIRECT ? 0 : 3) || !wino) break;
        }
        asm volatile("cp.async.bulk.wait_group.read 0;\n" ::: "memory");
        TS1(wid - 10, 24);
      } else {
        arrive_if(one ? bars + (B_SR + wg) * 8 : 0u);
      }
      TSDUMP(wid - 10);
    }
  }
}

typedef CUresult (*EncodeTiledFn)(CUtensorMap*, CUtensorMapDataType, cuuint32_t, void*, const cuuint64_t*,
                                  const cuuint64_t*, const cuuint32_t*, const cuuint32_t*, CUtensorMapInterleave,
                                  CUtensorMapSwizzle, CUtensorMapL2promotion, CUtensorMapFloatOOBfill);

}

extern "C" void kernel_launch(void* const* d_in, const int* in_sizes, int n_in, void* d_out, int out_size) {
  static EncodeTiledFn encode = nullptr;
  static void* scratch = nullptr;
  if (!encode) {
    cudaGetSymbolAddress(&scratch, g_scratch);
    void* fn = nullptr;
    cudaDriverEntryPointQueryResult qres;
    cudaGetDriverEntryPoint("cuTensorMapEncodeTiled", &fn, cudaEnableDefault, &qres);
    encode = (EncodeTiledFn)fn;
    cudaFuncSetAttribute(dcn_kernel, cudaFuncAttributeMaxDynamicSharedMemorySize, SMEM_BYTES);
  }
  Maps tm;
  const cuuint32_t es[5] = {1, 1, 1, 1, 1};
  constexpr cuuint64_t PX = IC * 2, ROW = IW * IC * 2;
  for (int i = 0; i < 4; i++) {
    const cuuint64_t dims[3] = {IC, IW, IH};
    const cuuint64_t strides[2] = {i == 2 ? ROW : PX, i == 2 ? PX : ROW};
    const cuuint32_t box[5][3] = {{32, 2, 34}, {32, 10, 20}, {32, 10, 20}, {32, 12, 12}, {32, 6, 34}};
    encode(&tm.x[i], CU_TENSOR_MAP_DATA_TYPE_BFLOAT16, 3, d_in[0], dims, strides, box[i], es, CU_TENSOR_MAP_INTERLEAVE_NONE,
           i & 3 ? CU_TENSOR_MAP_SWIZZLE_64B : CU_TENSOR_MAP_SWIZZLE_NONE, CU_TENSOR_MAP_L2_PROMOTION_NONE,
           CU_TENSOR_MAP_FLOAT_OOB_FILL_NONE);
  }
  {
    const cuuint64_t dims[4] = {IC, 2, IH, IW / 2 - 1};
    const cuuint64_t strides[3] = {PX, ROW, 2 * PX};
    const cuuint32_t box[4] = {32, 2, 34, 2};
    encode(&tm.x[4], CU_TENSOR_MAP_DATA_TYPE_BFLOAT16, 4, (char*)d_in[0] + PX, dims, strides, box, es, CU_TENSOR_MAP_INTERLEAVE_NONE,
           CU_TENSOR_MAP_SWIZZLE_NONE, CU_TENSOR_MAP_L2_PROMOTION_NONE, CU_TENSOR_MAP_FLOAT_OOB_FILL_NONE);
  }
  for (int i = 0; i < 2; i++) {
    const cuuint64_t dims[5] = {32, IC, 3, 3, 3};
    const cuuint64_t strides[4] = {IC * 2, 64, IC * IC * 2, 3 * IC * IC * 2};
    const cuuint32_t box[5] = {32, 16, 3, i ? 3u : 1u, i ? 1u : 3u};
    encode(&tm.w[i], CU_TENSOR_MAP_DATA_TYPE_BFLOAT16, 5, d_in[2], dims, strides, box, es, CU_TENSOR_MAP_INTERLEAVE_NONE,
           CU_TENSOR_MAP_SWIZZLE_64B, CU_TENSOR_MAP_L2_PROMOTION_L2_128B, CU_TENSOR_MAP_FLOAT_OOB_FILL_NONE);
  }
  for (int i = 0; i < 2; i++) {
    const cuuint64_t dims[2] = {IW * 9, IH};
    const cuuint64_t strides[1] = {IW * 36};
    const cuuint32_t box[2] = {i ? 72u : 144u, i ? 8u : 32u};
    encode(&tm.o[i], CU_TENSOR_MAP_DATA_TYPE_UINT32, 2, d_in[1], dims, strides, box, es, CU_TENSOR_MAP_INTERLEAVE_NONE,
           CU_TENSOR_MAP_SWIZZLE_NONE, CU_TENSOR_MAP_L2_PROMOTION_NONE, CU_TENSOR_MAP_FLOAT_OOB_FILL_NONE);
  }
  for (int i = 0; i < 5; i++) {
    const cuuint64_t dims[5] = {32, IW, i & 3 ? IH : 4u, i & 3 ? 1u : IH / 4, 3};
    const cuuint64_t strides[4] = {i == 2 ? ROW : PX, i == 2 ? PX : ROW, 4 * ROW, 64};
    const cuuint32_t box[5] = {32, 8, i == 3 ? 8u : i & 3 ? 16u : 1u, i & 3 ? 1u : i ? 2u : 8u, 3};
    encode(&tm.out[i], CU_TENSOR_MAP_DATA_TYPE_BFLOAT16, 5, d_out, dims, strides, box, es, CU_TENSOR_MAP_INTERLEAVE_NONE,
           CU_TENSOR_MAP_SWIZZLE_64B, CU_TENSOR_MAP_L2_PROMOTION_NONE, CU_TENSOR_MAP_FLOAT_OOB_FILL_NONE);
  }
  dcn_kernel<<<GRID, NTHREADS, SMEM_BYTES>>>((const __nv_bfloat16*)d_in[0], (const uint32_t*)d_in[1], (const uint4*)d_in[2],
                                             (Scratch*)scratch, 0u, tm);
}
```

```cpp
#include <cuda_runtime.h>
#include <cuda.h>
#include <cuda_bf16.h>
#include <stdint.h>

namespace {

constexpr int IH = 224, IW = 224, IC = 96;
constexpr int GRID = 132, NC = 12, NW = 72, NG = 48;
constexpr int NTHREADS = 512;
constexpr int STAGE = 18432;
constexpr int WTAP = 3072 >> 4, WHALF = (STAGE / 2) >> 4;
constexpr uint32_t SB = 0x400;
constexpr int VROW = 18 * 64, VSLOT = 8 * VROW, PIECE = 34 * 128;
constexpr int SM_R = 14 * VSLOT, SM_WW = SM_R + 39936;
constexpr int GROW = 10 * 64, GSLICE = 20 * GROW, GWIN = 3 * GSLICE, SM_GW = 2 * GWIN, SM_GO = SM_GW + 7 * STAGE, SM_GT = SM_GO + 9216;
constexpr int CROW = 12 * 64, CSLICE = 12 * CROW, CWIN = 3 * CSLICE, SM_CX = 9 * STAGE, SM_CT = SM_CX + 2 * CWIN;
constexpr int SM_FIX = 224256, SM_BAR = 231168, SMEM_BYTES = 232448;
constexpr int B_XF = 0;
constexpr int B_OG = 7;
constexpr int B_WF = 16;
constexpr int B_IM = 34;
constexpr int B_OF = 35;
constexpr int B_SR = 36;
constexpr int B_RD = 39;
constexpr int B_W2 = 96;
constexpr int B_WE = 40;
constexpr int B_WL = 56;
constexpr int B_V0 = 57;
constexpr int B_SG = 58;
constexpr int B_VE = 59;
constexpr int B_ST = 64;
constexpr int B_VF = 71;
constexpr int B_RE = 80;
constexpr int B_R2 = 85;
constexpr int B_PP = 86;
constexpr int O_CNT = 776, O_REC = 784, O_SEL = 912;
constexpr int NREC = 16;
constexpr uint32_t SDELAY = 2600, SDELAY2 = 500, PDELAY = 4600, FDELAY = 7000, IDELAY = 6000;
constexpr uint32_t GX0 = 1500, GX1 = 3200, GXS = 2300, GW0 = 1600, GWS = 750, CX0 = 1000, CXS = 2200, CW0 = 1000, CWS = 300;

struct Scratch {
  uint8_t u[8 * STAGE];
  uint4 fix[8 * NREC * 12];
  uint2 key[8 * NREC];
  uint32_t cnt[32];
  uint32_t launch[160];
};
__device__ __align__(128) Scratch g_scratch;

__device__ __forceinline__ float bf16lo(uint32_t v) { return __uint_as_float(v << 16); }
__device__ __forceinline__ float bf16hi(uint32_t v) { return __uint_as_float(v & 0xffff0000u); }
__device__ __forceinline__ uint32_t smem_u32(const void* p) { return (uint32_t)__cvta_generic_to_shared(p); }
__device__ __forceinline__ void mbar_init(uint32_t bar, uint32_t count) {
  asm volatile("mbarrier.init.shared::cta.b64 [%0], %1;\n" ::"r"(bar), "r"(count) : "memory");
}
__device__ __forceinline__ void mbar_expect_tx(uint32_t bar, uint32_t bytes) {
  asm volatile("mbarrier.arrive.expect_tx.shared::cta.b64 _, [%0], %1;\n" ::"r"(bar), "r"(bytes) : "memory");
}
__device__ __forceinline__ void mbar_wait(uint32_t bar, uint32_t parity = 0) {
  asm volatile(
      "{\n.reg .pred p;\n"
      "W_%=:\n"
      "mbarrier.try_wait.parity.shared::cta.b64 p, [%0], %1;\n"
      "@!p bra W_%=;\n}\n"
      ::"r"(bar), "r"(parity) : "memory");
}
__device__ __forceinline__ uint32_t mbar_poll(uint32_t bar) {
  uint32_t done;
  asm volatile(
      "{\n.reg .pred p;\n"
      "mbarrier.test_wait.parity.shared::cta.b64 p, [%1], 0;\n"
      "selp.u32 %0, 1, 0, p;\n}\n"
      : "=r"(done)
      : "r"(bar)
      : "memory");
  return done;
}
__device__ __forceinline__ uint32_t clock32() {
  uint32_t c;
  asm volatile("mov.u32 %0, %%clock;\n" : "=r"(c)::"memory");
  return c;
}
__device__ __forceinline__ int lane_now() {
  int l;
  asm volatile("mov.u32 %0, %%laneid;\n" : "=r"(l));
  return l;
}
__device__ __forceinline__ void wait_until(uint32_t t0, uint32_t dt) {
  while (clock32() - t0 < dt) __nanosleep(40);
}
__device__ __forceinline__ void tma_load_x(uint32_t dst, const CUtensorMap* tm, uint32_t bar, uint32_t bytes, int c0, int c1, int c2) {
  if (bytes) mbar_expect_tx(bar, bytes);
  asm volatile(
      "cp.async.bulk.tensor.3d.shared::cluster.global.mbarrier::complete_tx::bytes [%0], [%1, {%3, %4, %5}], [%2];\n" ::"r"(dst),
      "l"(reinterpret_cast<uint64_t>(tm)), "r"(bar), "r"(c0), "r"(c1), "r"(c2)
      : "memory");
}
__device__ __forceinline__ void tma_load_x4(uint32_t dst, const CUtensorMap* tm, uint32_t bar, int c, int y, int pair) {
  asm volatile(
      "cp.async.bulk.tensor.4d.shared::cluster.global.mbarrier::complete_tx::bytes [%0], [%1, {%3, %6, %4, %5}], [%2];\n" ::"r"(dst),
      "l"(reinterpret_cast<uint64_t>(tm)), "r"(bar), "r"(c), "r"(y), "r"(pair), "r"(0)
      : "memory");
}
__device__ __forceinline__ void tma_load_o(uint32_t dst, const CUtensorMap* tm, uint32_t bar, int x, int y) {
  asm volatile(
      "cp.async.bulk.tensor.2d.shared::cluster.global.mbarrier::complete_tx::bytes [%0], [%1, {%3, %4}], [%2];\n" ::"r"(dst),
      "l"(reinterpret_cast<uint64_t>(tm)), "r"(bar), "r"(x * 9), "r"(y)
      : "memory");
}
__device__ __forceinline__ void tma_load_w(uint32_t dst, const CUtensorMap* tm, uint32_t bar, int c, int kj, int ki, uint32_t mask) {
  asm volatile(
      "cp.async.bulk.tensor.5d.shared::cluster.global.mbarrier::complete_tx::bytes.multicast::cluster [%0], [%1, {%3, %4, "
      "%3, %5, %6}], [%2], %7;\n" ::"r"(dst),
      "l"(reinterpret_cast<uint64_t>(tm)), "r"(bar), "r"(0), "r"(c), "r"(kj), "r"(ki), "h"((uint16_t)mask)
      : "memory");
}
__device__ __forceinline__ void bulk_load_mc(uint32_t dst, const void* src, uint32_t bytes, uint32_t bar) {
  asm volatile(
      "cp.async.bulk.shared::cluster.global.mbarrier::complete_tx::bytes.multicast::cluster [%0], [%1], %2, [%3], %4;\n" ::"r"(dst),
      "l"(src), "r"(bytes), "r"(bar), "h"((uint16_t)3)
      : "memory");
}
__device__ __forceinline__ void tma_store(const CUtensorMap* tm, uint32_t src, int c1, int c2, int c3) {
  asm volatile("cp.async.bulk.tensor.5d.global.shared::cta.bulk_group [%0, {%2, %3, %4, %5, %2}], [%1];\n" ::"l"(
                   reinterpret_cast<uint64_t>(tm)),
               "r"(src), "r"(0), "r"(c1), "r"(c2), "r"(c3)
               : "memory");
  asm volatile("cp.async.bulk.commit_group;\n" ::: "memory");
}
__device__ __forceinline__ constexpr uint64_t w_desc(uint32_t saddr) {
  return (uint64_t)((saddr & 0x3FFFF) >> 4) | ((uint64_t)(1024 >> 4) << 16) | ((uint64_t)(512 >> 4) << 32) | ((uint64_t)2 << 62);
}
__device__ __forceinline__ constexpr uint64_t a_desc(uint32_t saddr) {
  return (uint64_t)((saddr & 0x3FFFF) >> 4) | ((uint64_t)1 << 16) | ((uint64_t)(VROW >> 4) << 32) | ((uint64_t)2 << 62);
}
#define ACC_OPERANDS(c, d)                                                                                        \
  c(d[0]), c(d[1]), c(d[2]), c(d[3]), c(d[4]), c(d[5]), c(d[6]), c(d[7]), c(d[8]),      \
      c(d[9]), c(d[10]), c(d[11]), c(d[12]), c(d[13]), c(d[14]), c(d[15]), c(d[16]),       \
      c(d[17]), c(d[18]), c(d[19]), c(d[20]), c(d[21]), c(d[22]), c(d[23]), c(d[24]),      \
      c(d[25]), c(d[26]), c(d[27]), c(d[28]), c(d[29]), c(d[30]), c(d[31]), c(d[32]),      \
      c(d[33]), c(d[34]), c(d[35]), c(d[36]), c(d[37]), c(d[38]), c(d[39]), c(d[40]),      \
      c(d[41]), c(d[42]), c(d[43]), c(d[44]), c(d[45]), c(d[46]), c(d[47])
#define ACC_LIST                                                                   \
  "{%0, %1, %2, %3, %4, %5, %6, %7, %8, %9, %10, %11, %12, %13, %14, %15, "        \
  "%16, %17, %18, %19, %20, %21, %22, %23, %24, %25, %26, %27, %28, %29, %30, %31, " \
  "%32, %33, %34, %35, %36, %37, %38, %39, %40, %41, %42, %43, %44, %45, %46, %47}, "
__device__ __forceinline__ void wgmma_ss(float* d, uint64_t adesc, uint64_t bdesc, uint32_t accumulate) {
  asm volatile(
      "{\n.reg .pred p;\nsetp.ne.b32 p, %50, 0;\n"
      "wgmma.mma_async.sync.aligned.m64n96k16.f32.bf16.bf16 " ACC_LIST "%48, %49, p, 1, 1, 0, 1;\n}\n"
      : ACC_OPERANDS("+f", d)
      : "l"(adesc), "l"(bdesc), "r"(accumulate));
}
__device__ __forceinline__ void wgmma_def(float* d, uint64_t desc, uint32_t on) {
  asm volatile(
      "{\n.reg .pred p, q;\nsetp.ne.b32 p, 0, 0;\nsetp.ne.b32 q, %49, 0;\n"
      "@q wgmma.mma_async.sync.aligned.m64n96k16.f32.bf16.bf16 " ACC_LIST "%48, %48, p, 1, 1, 1, 1;\n}\n"
      : ACC_OPERANDS("=f", d)
      : "l"(desc), "r"(on));
}
__device__ __forceinline__ void wgmma_rs(float* d, const uint32_t* a, uint64_t bdesc, uint32_t accumulate = 1) {
  asm volatile(
      "{\n.reg .pred p;\nsetp.ne.b32 p, %53, 0;\n"
      "wgmma.mma_async.sync.aligned.m64n96k16.f32.bf16.bf16 " ACC_LIST "{%48, %49, %50, %51}, %52, p, 1, 1, 1;\n}\n"
      : ACC_OPERANDS("+f", d)
      : "r"(a[0]), "r"(a[1]), "r"(a[2]), "r"(a[3]), "l"(bdesc), "r"(accumulate));
}
__device__ __forceinline__ void wgmma_fence() { asm volatile("wgmma.fence.sync.aligned;\n" ::: "memory"); }
__device__ __forceinline__ void wgmma_commit() { asm volatile("wgmma.commit_group.sync.aligned;\n" ::: "memory"); }
template <int N>
__device__ __forceinline__ void wgmma_wait() { asm volatile("wgmma.wait_group.sync.aligned %0;\n" ::"n"(N) : "memory"); }
__device__ __forceinline__ void acc_fence(float* d) {
#pragma unroll
  for (int i = 0; i < 48; i++) asm volatile("" : "+f"(d[i])::"memory");
}
#define UPD(text, d, e, c) asm volatile("{\n.reg .pred p;\nsetp.eq.u32 p, %3, 0;\n@p " text ";\n}\n" : "+f"(d) : "f"(e), "f"(c), "r"(guard))
#define UPD_ADD(d, e, c) UPD("fma.rn.f32 %0, %1, %2, %0", d, e, c)
#define UPD_MUL(d, e, c) UPD("fma.rn.f32 %0, %0, %2, %1", d, e, c)
__device__ __forceinline__ void keep_alive8(const uint32_t* a, uint32_t never) {
  asm volatile(
      "{\n.reg .pred p, q;\nsetp.eq.u32 p, %8, 16;\nsetp.eq.u32 q, %8, 32;\n"
      "@p st.shared.v4.b32 [%8], {%0, %1, %2, %3};\n@q st.shared.v4.b32 [%8], {%4, %5, %6, %7};\n}\n" ::"r"(a[0]),
      "r"(a[1]), "r"(a[2]), "r"(a[3]), "r"(a[4]), "r"(a[5]), "r"(a[6]), "r"(a[7]), "r"(never)
      : "memory");
}
__device__ __forceinline__ void keep_alive4(const uint32_t* a, uint32_t never) {
  asm volatile("{\n.reg .pred p;\nsetp.eq.u32 p, %4, 16;\n@p st.shared.v4.b32 [%4], {%0, %1, %2, %3};\n}\n" ::"r"(a[0]), "r"(a[1]), "r"(a[2]),
               "r"(a[3]), "r"(never) : "memory");
}
__device__ __forceinline__ void ldsm4(uint32_t& r0, uint32_t& r1, uint32_t& r2, uint32_t& r3, uint32_t addr) {
  asm volatile("ldmatrix.sync.aligned.m8n8.x4.shared.b16 {%0, %1, %2, %3}, [%4];\n"
               : "=r"(r0), "=r"(r1), "=r"(r2), "=r"(r3)
               : "r"(addr)
               : "memory");
}
__device__ __forceinline__ void ldsm4(uint32_t* r, uint32_t addr) { ldsm4(r[0], r[1], r[2], r[3], addr); }
__device__ __forceinline__ void stsm4(uint32_t addr, const uint32_t* r) {
  asm volatile("stmatrix.sync.aligned.m8n8.x4.shared.b16 [%0], {%1, %2, %3, %4};\n" ::"r"(addr), "r"(r[0]), "r"(r[1]), "r"(r[2]), "r"(r[3])
               : "memory");
}
__device__ __forceinline__ void arrive_if(uint32_t bar) {
  asm volatile("{\n.reg .pred p;\nsetp.ne.u32 p, %0, 0;\n@p mbarrier.arrive.shared::cluster.b64 _, [%0];\n}\n" ::"r"(bar) : "memory");
}
__device__ __forceinline__ uint32_t lds32(uint32_t addr) {
  uint32_t v;
  asm volatile("ld.shared.u32 %0, [%1];\n" : "=r"(v) : "r"(addr) : "memory");
  return v;
}
__device__ __forceinline__ void lds64(uint32_t& a, uint32_t& b, uint32_t addr) {
  asm volatile("ld.shared.v2.u32 {%0, %1}, [%2];\n" : "=r"(a), "=r"(b) : "r"(addr) : "memory");
}
__device__ __forceinline__ void lds128(uint32_t* v, uint32_t addr) {
  asm volatile("ld.shared.v4.b32 {%0, %1, %2, %3}, [%4];\n" : "=r"(v[0]), "=r"(v[1]), "=r"(v[2]), "=r"(v[3]) : "r"(addr) : "memory");
}
__device__ __forceinline__ void sts128(uint32_t addr, const uint32_t* v) {
  asm volatile("st.shared.v4.b32 [%0], {%1, %2, %3, %4};\n" ::"r"(addr), "r"(v[0]), "r"(v[1]), "r"(v[2]), "r"(v[3]) : "memory");
}
__device__ __forceinline__ void sts64(uint32_t addr, const uint32_t* v) {
  asm volatile("st.shared.v2.b32 [%0], {%1, %2};\n" ::"r"(addr), "r"(v[0]), "r"(v[1]) : "memory");
}
__device__ __forceinline__ void sts32(uint32_t addr, uint32_t v) {
  asm volatile("st.shared.u32 [%0], %1;\n" ::"r"(addr), "r"(v) : "memory");
}
__device__ __forceinline__ void fence_async() { asm volatile("fence.proxy.async.shared::cta;\n" ::: "memory"); }
__device__ __forceinline__ void bar_sync(int id, int n) { asm volatile("bar.sync %0, %1;\n" ::"r"(id), "r"(n) : "memory"); }
__device__ __forceinline__ __nv_bfloat162 as_bf2(uint32_t v) { return *reinterpret_cast<__nv_bfloat162*>(&v); }
__device__ __forceinline__ uint32_t as_u32(__nv_bfloat162 v) { return *reinterpret_cast<uint32_t*>(&v); }
__device__ __forceinline__ uint32_t hfma2(uint32_t c, uint32_t a, uint32_t b) { return as_u32(__hfma2(as_bf2(c), as_bf2(a), as_bf2(b))); }
__device__ __forceinline__ uint32_t hadd2(uint32_t a, uint32_t b) { return as_u32(__hadd2(as_bf2(a), as_bf2(b))); }
__device__ __forceinline__ uint32_t hsub2(uint32_t a, uint32_t b) { return as_u32(__hsub2(as_bf2(a), as_bf2(b))); }
__device__ __forceinline__ __nv_bfloat162 half_of(uint32_t w, int hi) { return hi ? __high2bfloat162(as_bf2(w)) : __low2bfloat162(as_bf2(w)); }
__device__ __forceinline__ uint32_t hmul2_h(uint32_t w, int hi, uint32_t a) { return as_u32(__hmul2(half_of(w, hi), as_bf2(a))); }
__device__ __forceinline__ uint32_t hfma2_h(uint32_t w, int hi, uint32_t a, uint32_t c) {
  return as_u32(__hfma2(half_of(w, hi), as_bf2(a), as_bf2(c)));
}
__device__ __forceinline__ uint32_t pack2(float lo, float hi) { return as_u32(__floats2bfloat162_rn(lo, hi)); }
__device__ __forceinline__ uint32_t prmt(uint32_t a, uint32_t b, uint32_t sel) {
  uint32_t r;
  asm("prmt.b32 %0, %1, %2, %3;\n" : "=r"(r) : "r"(a), "r"(b), "r"(sel));
  return r;
}
__device__ __forceinline__ uint32_t absmax2(uint32_t a, uint32_t b) {
  uint32_t r;
  asm("max.NaN.xorsign.abs.bf16x2 %0, %1, %2;\n" : "=r"(r) : "r"(a), "r"(b));
  return r;
}
__device__ __forceinline__ uint32_t clip2(uint32_t p) {
  return as_u32(__hmin2(__hmax2(as_bf2(p), as_bf2(0u)), as_bf2(0x435f435fu)));
}
__device__ __forceinline__ constexpr uint32_t tap_delta(int a, int b) {
  return (a == 0 ? 0xbf80u : a == 1 ? 0u : 0x3f80u) | (b == 0 ? 0xbf800000u : b == 1 ? 0u : 0x3f800000u);
}
__device__ __forceinline__ void coefs(uint32_t w, uint32_t& p0, uint32_t& p1) {
  const uint32_t o = hsub2(0x3f803f80u, w);
  const uint32_t xa = __byte_perm(o, w, 0x7632);
  p0 = hmul2_h(o, 0, xa);
  p1 = hmul2_h(w, 0, xa);
}
__device__ __forceinline__ uint32_t frac2(uint32_t pos) {
  const float py = bf16lo(pos), px = bf16hi(pos);
  return __byte_perm(__float_as_uint(py - floorf(py)), __float_as_uint(px - floorf(px)), 0x7632);
}
__device__ __forceinline__ void blend4(uint32_t* t, const uint32_t* g, const uint32_t* h, const uint32_t* k, uint32_t a0,
                                       uint32_t a1, uint32_t b0, uint32_t b1) {
#pragma unroll
  for (int i = 0; i < 4; i++) {
    const uint32_t p0 = (i & 1) ? b0 : a0, p1 = (i & 1) ? b1 : a1;
    t[i] = hfma2_h(p1, 1, k[i], hfma2_h(p1, 0, h[i], hfma2_h(p0, 1, g[i], hmul2_h(p0, 0, t[i]))));
  }
}
__device__ __forceinline__ bool elect_one() {
  uint32_t r;
  asm volatile("{\n.reg .pred p;\nelect.sync _|p, 0xffffffff;\nselp.u32 %0, 1, 0, p;\n}\n" : "=r"(r));
  return r != 0;
}

template <int N>
__device__ __forceinline__ void transform6(const uint32_t (*d)[N], uint32_t dst, uint32_t off0) {
  uint32_t v[N], t[N], u[N];
  auto put = [&](int slot, const uint32_t* r) {
    const uint32_t a = slot < 4 ? dst + slot * VSLOT : dst + off0 + (slot - 4) * VSLOT;
    if (N == 4) sts128(a, r);
    else sts64(a, r);
  };
#pragma unroll
  for (int k = 0; k < 2; k++) {
#pragma unroll
    for (int i = 0; i < N; i++) v[i] = hfma2(0xc088c088u, d[2 + k][i], hadd2(d[k][i], d[4 + k][i]));
    put(4 + k, v);
  }
#pragma unroll
  for (int k = 0; k < 2; k++) {
    const uint32_t c = k ? 0xbe80be80u : 0xc080c080u, f = k ? 0x40004000u : 0x3f003f00u;
#pragma unroll
    for (int i = 0; i < N; i++) {
      t[i] = hfma2(c, d[2][i], d[4][i]);
      u[i] = hfma2(c, d[1][i], d[3][i]);
      v[i] = hfma2(f, u[i], t[i]);
    }
    put(2 * k, v);
#pragma unroll
    for (int i = 0; i < N; i++) t[i] = hfma2(f ^ 0x80008000u, u[i], t[i]);
    put(2 * k + 1, t);
  }
}

template <bool FP32>
__device__ __forceinline__ void weights4(const uint32_t* g0, const uint32_t* g1, const uint32_t* g2, uint32_t (*u)[4]) {
#pragma unroll
  for (int i = 0; i < 4; i++) {
    if (FP32) {
      float r[4][2];
#pragma unroll
      for (int h = 0; h < 2; h++) {
        const float a = h ? bf16hi(g0[i]) : bf16lo(g0[i]), b = h ? bf16hi(g1[i]) : bf16lo(g1[i]), c = h ? bf16hi(g2[i]) : bf16lo(g2[i]);
        const float ea = fmaf(0.25f, c, a) * -0.5f, eb = fmaf(0.25f, a, c);
        r[0][h] = fmaf(-0.25f, b, ea);
        r[1][h] = fmaf(0.25f, b, ea);
        r[2][h] = fmaf(0.5f, b, eb);
        r[3][h] = fmaf(-0.5f, b, eb);
      }
#pragma unroll
      for (int k = 0; k < 4; k++) u[k][i] = pack2(r[k][0], r[k][1]);
    } else {
      const uint32_t ea = hfma2(0xbe00be00u, g2[i], as_u32(__hmul2(as_bf2(g0[i]), as_bf2(0xbf00bf00u))));
      u[0][i] = hfma2(0xbe80be80u, g1[i], ea);
      u[1][i] = hfma2(0x3e803e80u, g1[i], ea);
      const uint32_t eb = hfma2(0x3e803e80u, g0[i], g2[i]);
      u[2][i] = hfma2(0x3f003f00u, g1[i], eb);
      u[3][i] = hfma2(0xbf00bf00u, g1[i], eb);
    }
  }
}

template <int GROUP = 4096>
__device__ __forceinline__ void stage_slab(const float* acc, uint32_t stg, int lane) {
  const uint32_t a = stg + (lane & 15) * 64 + (((lane >> 4) ^ ((lane >> 1) & 3)) << 4);
#pragma unroll
  for (int jp = 0; jp < 6; jp++) {
    uint32_t pk[4];
#pragma unroll
    for (int i = 0; i < 4; i++) pk[i] = pack2(acc[jp * 8 + i * 2], acc[jp * 8 + i * 2 + 1]);
    stsm4((a ^ ((jp & 1) * 32)) + (jp >> 1) * GROUP, pk);
  }
}
__device__ __forceinline__ void publish(uint32_t bar, int lane) {
  fence_async();
  __syncwarp();
  arrive_if(lane == 0 ? bar : 0u);
}
__device__ __forceinline__ constexpr uint32_t w_slot(int st) {
  return st < 3 ? SM_WW + st * STAGE : st == 3 ? 12 * VSLOT : st < 11 ? SM_WW + (st - 4) % 3 * STAGE : st < 13 ? 4 * VSLOT + (st - 11) * STAGE
         : st < 16 ? SM_WW + st % 3 * STAGE : st == 16 ? 4 * VSLOT : STAGE;
}
__device__ __forceinline__ constexpr uint64_t w_slots(int st0, int step, int n) {
  uint64_t r = 0;
  for (int i = 0; i < n; i++) r |= (uint64_t)(w_slot(st0 + i * step) >> 10) << (8 * i);
  return r;
}
__device__ __forceinline__ uint32_t w_stg(int wg, int i) {
  return wg ? (i == 2 ? 0 : i == 1 ? SM_R + 24576 : i == 0 ? 4 * VSLOT + STAGE : SM_WW + STAGE) : SM_R + (i == 2 ? 24576 : (i & 1) * 12288);
}

__device__ __forceinline__ void ldsm4_if(uint32_t* r, uint32_t addr, uint32_t on) {
  asm volatile(
      "{\n.reg .pred p;\nsetp.ne.u32 p, %5, 0;\n"
      "@p ldmatrix.sync.aligned.m8n8.x4.shared.b16 {%0, %1, %2, %3}, [%4];\n}\n"
      : "+r"(r[0]), "+r"(r[1]), "+r"(r[2]), "+r"(r[3])
      : "r"(addr), "r"(on)
      : "memory");
}
__device__ __forceinline__ void push_record(uint32_t bars, uint32_t key, uint32_t pos) {
  uint32_t slot;
  asm volatile("atom.shared.add.u32 %0, [%1], 1;\n" : "=r"(slot) : "r"(bars + O_CNT) : "memory");
  const uint32_t v[2] = {key, pos};
  if (slot < NREC) sts64(bars + O_REC + slot * 8, v);
}
__device__ __forceinline__ void put_sel(uint32_t bars, uint32_t key, int lane) {
  if (lane < NREC)
    asm volatile("st.shared.u16 [%0], %1;\n" ::"r"(bars + O_SEL + (lane & 6) * 4 + (lane >> 3) * 4 + (lane & 1) * 2), "h"((uint16_t)((key >> 20) | 0x4000u)) : "memory");
}
__device__ __noinline__ void push_taps(uint32_t bars, uint32_t key, uint32_t taps, const uint32_t* __restrict__ offs) {
  const int y = key & 255, x = (key >> 8) & 255;
#pragma unroll 1
  for (; taps; taps &= taps - 1) {
    const int tap = __ffs(taps) - 1, ki = (tap * 11) >> 5;
    const uint32_t gp = pack2((float)(y + ki - 1), (float)(x + tap - ki * 3 - 1));
    push_record(bars, key | (tap << 16), clip2(hadd2(gp, __ldg(offs + (y * IW + x) * 9 + tap))));
  }
}
__device__ __forceinline__ uint32_t wino_key(int y, int x) {
  return y | (x << 8) | ((((y & 28) << 1) | (x & 7)) << 20) | ((((x & 8) >> 1) | (y & 3)) << 27);
}
__device__ __forceinline__ uint32_t strip_key(int u, int v, int left) {
  return (left ? v | (u << 8) : u | (v << 8)) | ((((u & 15) << 3) | (v & 7)) << 20) | ((u >> 4) << 29);
}
__device__ __forceinline__ bool strip_off(uint32_t d, bool out) { return (d & 0x7fff) || (d & 0x7fff7fffu) > (out ? 0u : 0x3f000000u); }
__device__ __forceinline__ void delta(uint32_t* v, uint32_t key, uint32_t pos, const uint4* __restrict__ x, int c) {
  const int tap = (key >> 16) & 15, ki = (tap * 11) >> 5, gy = (int)bf16lo(pos), gx = (int)bf16hi(pos);
  const int cy = min(max((int)(key & 255) + ki - 1, 0), IH - 1), cx = min(max((int)((key >> 8) & 255) + tap - ki * 3 - 1, 0), IW - 1);
  const uint32_t sx = gx < IW - 1 ? 12 : 0, sy = gy < IH - 1 ? IW * 12 : 0, p = (gy * IW + gx) * 12 + c;
  uint4 t[5] = {__ldg(x + p), __ldg(x + (p + sx)), __ldg(x + (p + sy)), __ldg(x + (p + sy + sx)), __ldg(x + (uint32_t)((cy * IW + cx) * 12 + c))};
  uint32_t q0, q1;
  coefs(frac2(pos), q0, q1);
  blend4(&t[0].x, &t[1].x, &t[2].x, &t[3].x, q0, q1, q0, q1);
#pragma unroll
  for (int i = 0; i < 4; i++) v[i] = hsub2((&t[0].x)[i], (&t[4].x)[i]);
}
__device__ __forceinline__ void fixup(uint32_t bars, int w, int n, const uint4* __restrict__ x, const uint4* __restrict__ wgt) {
  const uint32_t fix = bars + SM_FIX - SM_BAR + 3072, part = fix + 3072;
  const int lane = lane_now(), l = min(lane, 23), up = l >= 12;
#pragma unroll 1
  for (int r = 0; r < n; r++) {
    uint32_t key, pos, sum[4];
    lds64(key, pos, bars + O_REC + r * 8);
    key = __shfl_sync(0xffffffffu, key, 0);
    pos = __shfl_sync(0xffffffffu, pos, 0);
    delta(sum, key, pos, x, w * 3 + (l >> 3));
    sts128(part + w * 192 + (l >> 3) * 16, sum);
    __syncwarp();
#pragma unroll
    for (int i = 0; i < 4; i++) sum[i] = 0;
    const uint4* wp = wgt + (((key >> 16) & 15) * 96 + w * 24 + up * 11) * 12 + l;
#pragma unroll 1
    for (int h = 0; h < 3; h++) {
      uint4 wv[4];
      uint32_t d[2];
#pragma unroll
      for (int k = 0; k < 4; k++) wv[k] = __ldg(wp + (h * 4 + k) * 12);
      lds64(d[0], d[1], part + w * 192 + up * 24 + h * 8);
#pragma unroll
      for (int i = 0; i < 4; i++)
        sum[i] = hadd2(sum[i], hfma2_h(d[1], 1, (&wv[3].x)[i], hfma2_h(d[1], 0, (&wv[2].x)[i], hfma2_h(d[0], 1, (&wv[1].x)[i], hmul2_h(d[0], 0, (&wv[0].x)[i])))));
    }
#pragma unroll
    for (int i = 0; i < 4; i++) sum[i] = hadd2(sum[i], __shfl_down_sync(0xffffffffu, sum[i], 12));
    if (lane < 12) sts128(part + w * 192 + lane * 16, sum);
    bar_sync(4, 128);
    if (lane < 12) {
      float lo = 0.0f, hi = 0.0f;
#pragma unroll
      for (int k = 0; k < 4; k++) {
        const uint32_t v = lds32(part + k * 192 + w * 48 + lane * 4);
        lo += bf16lo(v);
        hi += bf16hi(v);
      }
      sts32(fix + r * 192 + w * 48 + lane * 4, pack2(lo, hi));
    }
    bar_sync(4, 128);
  }
}
__device__ __forceinline__ void select_rows(uint32_t* A, const uint32_t* sel, uint32_t code, bool scale) {
#pragma unroll
  for (int i = 0; i < 4; i++) {
    A[i] = as_u32(__heq2(as_bf2(sel[i >> 1]), as_bf2(code + (i & 1) * 0x80008u)));
    if (scale) A[i] = as_u32(__hmul2(as_bf2(A[i]), as_bf2(0x3ff03ff0u)));
  }
}
struct Maps {
  CUtensorMap x[5];
  CUtensorMap w[2];
  CUtensorMap o[2];
  CUtensorMap out[4];
};

__global__ void __cluster_dims__(2, 1, 1) __launch_bounds__(NTHREADS, 1)
dcn_kernel(const __nv_bfloat16* __restrict__ x, const uint32_t* __restrict__ offs, const uint4* __restrict__ wgt, Scratch* scr,
           const uint32_t never, const __grid_constant__ Maps tm) {
  extern __shared__ __align__(1024) uint8_t smem[];
  const uint32_t sbase = smem_u32(smem);
  const uint32_t bars = sbase + SM_BAR;
  const uint32_t tstart = clock32();
  const int tid = threadIdx.x;
  const int cta = blockIdx.x - NC;
  const int wid = __shfl_sync(0xffffffffu, tid >> 5, 0);
  const int lane = tid & 31;
  const bool wino = (uint32_t)cta < NW, strip = cta >= NW;
  const int left = (uint32_t)cta >= NW + NG / 2;
  const int ry = (cta * 43) >> 9;
  const int x0 = wino ? 32 + (cta - ry * 12) * 16 : 32 + (cta - NW - left * (NG / 2)) * 8, y0 = 32 + ry * 32;
  auto load_cols = [&](int s, int j) {
    const uint32_t dst = sbase + (s ? SM_R : 4 * VSLOT) + j * 2 * PIECE, bar = bars + (B_XF + s * 5 + j) * 8;
    if (j < 4) tma_load_x4(dst, &tm.x[4], bar, s * 32, y0 - 1, (x0 >> 1) - 1 + j * 2);
    else tma_load_x(dst, &tm.x[0], bar, 0, s * 32, x0 + 15, y0 - 1);
  };
  auto corner_tile = [&](int wg) {
    const uint32_t t = ((wg ? 0xfeba00000000ull : 0xd976c8325410ull) >> (4 * (cta + NC))) & 15;
    return (t & 3) | ((t >> 2) << 8);
  };
  auto load_cx = [&](int wg, int g, uint32_t tl) {
    tma_load_x(sbase + SM_CX + wg * CWIN + g * CSLICE, &tm.x[3], bars + (B_XF + wg * 3 + g) * 8, CSLICE, g * 32, (int)(tl & 255) * 8 - 2,
               (int)(tl >> 8) * 8 - 2);
  };
  const bool one = elect_one();
  if (wid == 0 && one) {
    asm volatile("prefetch.tensormap [%0];\n" ::"l"(reinterpret_cast<uint64_t>(wino ? &tm.x[4] : &tm.o[1])) : "memory");
    asm volatile("prefetch.tensormap [%0];\n" ::"l"(reinterpret_cast<uint64_t>(&tm.x[0])) : "memory");
  }
  if (wid == 15) {
    if (one) {
      if (wino) {
        mbar_init(bars + B_W2 * 8, 1);
#pragma unroll
        for (int k = 0; k < 9; k++)
          asm volatile("cp.async.bulk.shared::cluster.global.mbarrier::complete_tx::bytes [%0], [%1], 6144, [%2];\n" ::"r"(sbase + k * 6144 + (k < 6 ? 0 : 6 * VSLOT)),
                       "l"(wgt + k * 1152), "r"(bars + B_W2 * 8) : "memory");
      }
#pragma unroll
      for (int j = 0; j < 8; j++) mbar_init(bars + j * 8, 1);
      if (wino) {
#pragma unroll
        for (int j = 0; j < 5; j++) load_cols(0, j);
        mbar_expect_tx(bars + B_W2 * 8, 9 * 6144);
      } else {
        mbar_expect_tx(bars + B_OG * 8, strip ? 4 * 2304 : 2 * 2304);
#pragma unroll
        for (int k = 0; k < 4; k++) {
          const uint32_t tl = corner_tile(k & 1);
          if (strip || k < 2)
            tma_load_o(sbase + (strip ? SM_GO + k * 2304 : SM_CX + k * CWIN + 2 * CSLICE), &tm.o[1], bars + B_OG * 8,
                       strip ? (left ? k * 8 : x0) : (tl & 255) * 8, strip ? (left ? x0 : k * 8) : (tl >> 8) * 8);
        }
        if (strip) {
          asm volatile("prefetch.tensormap [%0];\n" ::"l"(reinterpret_cast<uint64_t>(&tm.x[1 + left])) : "memory");
        } else {
          load_cx(0, 0, corner_tile(0));
          if (cta >= -4) load_cx(1, 0, corner_tile(1));
        }
        asm volatile("prefetch.tensormap [%0];\n" ::"l"(reinterpret_cast<uint64_t>(&tm.w[left])) : "memory");
      }
      asm volatile("fence.mbarrier_init.release.cluster;\n" ::: "memory");
    }
    __syncwarp();
  }
  const bool prep = wid >= 8 && wid < 11 && strip && cta < NW + 24;
  uint4 g[3];
  if (prep) {
    const uint4* src = wgt + (uint32_t)((cta - NW + ((cta - NW) >> 3) * 4) * 96 + 352 + (tid >> 5) * 4 + (lane >> 2) * 12 + (lane & 3));
#pragma unroll
    for (int k = 0; k < 3; k++) g[k] = __ldg(src + k * 3456);
  }
  if (wid < 8 || wid >= 12) {
    if (one && wid < 15) {
      const int grp = wid < 8 ? 4 + wid : 15 - wid;
#pragma unroll
      for (int i = 0; i < 8; i++) mbar_init(bars + grp * 64 + i * 8, grp < 5 ? 1 : grp < 7 ? 16 : grp < 8 ? 8 : 4);
      asm volatile("fence.mbarrier_init.release.cluster;\n" ::: "memory");
    }
    __syncwarp();
  } else if (one && wid == 11) {
    const uint32_t z[2] = {0, 1u << 31};
    sts64(bars + O_CNT, z);
    __threadfence_block();
  }
  asm volatile("barrier.cluster.arrive.relaxed.aligned;\n" ::: "memory");
  auto load_cw = [&](int st) {
    const uint32_t rank = cta & 1;
    const int g = (st * 11) >> 5;
    const uint32_t fb = bars + (B_WF + st) * 8;
    mbar_expect_tx(fb, STAGE);
    tma_load_w(sbase + st * STAGE, &tm.w[1], fb, g * 32, 0, st - g * 3, 1u << rank);
    tma_load_w(sbase + st * STAGE + STAGE / 2, &tm.w[1], fb, g * 32 + 16, 0, st - g * 3, 1u << rank);
  };
  if (wid < 8) {
    const int wg = wid >> 2, warp = wid & 3, lane = lane_now();
    if ((sbase & 0xffffff) != SB) __trap();
    const int src = cta + NC, t = tid & 127;
    const int lf = src == 0 || src == 7 ? t < 64 : src >= 4;
    const int along = ((0x0c84b842u >> (4 * src)) & 15) * 16 + (src == 0 || src == 7 ? (t >> 1) & 31 : t >> 1);
    const int oy = lf ? along : 32 + (t & 1), ox = lf ? 32 + (t & 1) : along;
    const bool own = src == 0 ? !lf || along >= 34 : along < (src == 2 ? 176 : 224);
    uint32_t o2[9], tag;
    if (src < 8 && wg) {
      tag = scr->launch[blockIdx.x] + 1;
#pragma unroll
      for (int m = 0; m < 9; m++) o2[m] = __ldg(offs + (min(oy, IH - 1) * IW + min(ox, IW - 1)) * 9 + m);
    }
    asm volatile("setmaxnreg.inc.sync.aligned.u32 224;\n");
    asm volatile("barrier.cluster.wait.acquire.aligned;\n" ::: "memory");
    uint32_t we_addr;
    asm volatile("mapa.shared::cluster.u32 %0, %1, %2;\n" : "=r"(we_addr) : "r"(bars + B_WE * 8), "r"(lane & 1));
    const uint32_t nv = never & (uint32_t)tid;
    float acc[4][48];
    int ntiles = 0;
    uint32_t tile0 = 0, tstep = 0;
    if (wino) {
      {
        const uint32_t dst = sbase + (wid & 2) * (STAGE / 4) + (wid & 1) * 512 + (lane >> 2) * 64 + (((lane ^ (lane >> 3)) & 3) << 4);
        const uint32_t src = sbase + warp * 1536 + (lane >> 2) * 192 + (lane & 3) * 16;
        mbar_wait(bars + B_W2 * 8);
        uint32_t gg[3][4], u[4][4];
        auto get = [&](int n) {
          const uint32_t a = src + n * 64 + ((n * 11) >> 5) * (6144 - 192);
          lds128(gg[0], a);
          lds128(gg[2], a + 10 * VSLOT);
          lds128(gg[1], a + 18432);
        };
        get(wg);
#pragma unroll 1
        for (int n = wg; n < 9; n += 2) {
          weights4<false>(gg[0], gg[1], gg[2], u);
          if (n < 7) get(n + 2);
#pragma unroll
          for (int k = 0; k < 4; k++) sts128(dst + n * 1024 + w_slot(k), u[k]);
        }
        fence_async();
        bar_sync(12, 384);
      }
      {
        const int q = wid + wg, tp = lane >> 3, h = tp * 18 + q;
        const uint32_t src = (sbase + 4 * VSLOT + q * PIECE + tp * 1024 + (lane & 7) * 16) & (x0 + 2 * q == IW ? ~64u : ~0u);
        const uint32_t vb = sbase + h * 128 + (lane & 4) * 16;
        mbar_wait(bars + (B_XF + (q >> 1)) * 8);
        uint32_t d[10][4];
#pragma unroll
        for (int r = 0; r < 9; r++) lds128(d[r], src + r * 128);
        lds128(d[9], src + (y0 + 32 == IH && tp == 3 ? 8 * 128 : 9 * 128));
        transform6<4>(d, vb + (((lane ^ h) & 3) << 4), 10 * VSLOT);
        transform6<4>(d + 4, vb + VROW + (((lane ^ (h + 1)) & 3) << 4), 10 * VSLOT);
        publish(bars + (wg ? B_VF + 1 : B_V0) * 8, lane);
      }
      constexpr uint64_t bd0 = w_desc(SB);
      const uint64_t ad0 = a_desc(SB) + wg * 32;
      uint32_t rel = 0;
      if (lane == 3) we_addr = bars + (B_VE - 3) * 8;
      if (lane == 2) we_addr = bars + (B_WL - 13) * 8;
      uint32_t guard = never, gnext = never;
#define PIN_NEXT do { guard = gnext; gnext = clock32() & never; } while (0)
      auto stage = [&](float* a, int st, uint32_t rs, int vslot, uint32_t accumulate, auto work, bool retire = true, bool await = true) {
        const uint64_t bd = bd0 + (rs >> 4), ad = ad0 + vslot * (VSLOT >> 4);
        if (await) mbar_wait(bars + (B_WF + st) * 8);
        wgmma_fence();
#pragma unroll
        for (int j = 0; j < 6; j++) {
          wgmma_ss(a, ad + (j >> 1) * 4 + (j & 1) * 2, bd + (j >> 1) * WTAP + (j & 1) * WHALF, j ? 1 : accumulate);
          if (j == 1 && retire) {
            wgmma_commit();
            wgmma_wait<1>();
            arrive_if(rel);
            rel = ((lane < 2 ? 0xff7u : lane == 3 ? 8u : lane == 2 ? 0x2000u : 0u) >> st) & 1 ? we_addr + st * 8 : 0u;
          }
          if (j == 5) wgmma_commit();
          work(j);
        }
      };
#pragma unroll
      for (int p = 0; p < 4; p++) {
        wgmma_fence();
        wgmma_def(acc[p], w_desc(SB + SM_WW), never);
      }
      wgmma_commit();
      mbar_wait(bars + B_V0 * 8);
      if (wg) mbar_wait(bars + (B_VF + 1) * 8);
#pragma unroll 1
      for (int s = 0; s < 3; s++) {
        if (s) {
          const uint32_t vf = bars + (B_VF + 2 * s + wg) * 8;
          if (!__all_sync(0xffffffffu, mbar_poll(vf)) || (wg && s == 2)) {
            wgmma_wait<0>();
            arrive_if(rel);
            rel = 0;
            if (wg && s == 2) mbar_wait(bars + B_PP * 8);
            mbar_wait(vf);
          }
        }
#pragma unroll
        for (int p = 0; p < 4; p++) {
          stage(acc[p], s * 4 + p, (((uint32_t)w_slots(p, 4, 3) >> (8 * s)) & 255) << 10, (s & 1) * 4 + p, s, [&](int j) {
            if (p == 3 && j == 1) arrive_if(lane == 0 && !wg && s == 2 ? bars + B_PP * 8 : 0u);
          });
        }
      }
      mbar_wait(bars + (B_WF + 12) * 8);
      uint32_t imp = lds32(bars + O_CNT + 4);
#pragma unroll
      for (int i = 0; i < 48; i++) {
        if (i % 8 == 0) PIN_NEXT;
        UPD_ADD(acc[0][i], acc[1][i], 1.0f);
        UPD_MUL(acc[1][i], acc[0][i], -2.0f);
      }
      wgmma_wait<0>();
      arrive_if(rel);
      rel = 0;
      imp = __ballot_sync(0xffffffffu, (imp >> lane) & 1);
      uint32_t sel[2], A[4];
      if ((imp >> (wg * 4)) & ~0xf0f0u) {
        mbar_wait(bars + B_IM * 8);
        if ((int)imp < 0) imp = __ballot_sync(0xffffffffu, (lds32(bars + O_CNT + 4) >> lane) & 1);
        lds64(sel[0], sel[1], bars + O_SEL + (lane & 3) * 8);
      }
      const uint32_t code = (wg * 512 + warp * 16 + (lane >> 2) + 0x4000u) * 0x10001u;
      auto corr = [&](int p) {
#pragma unroll
        for (int i = 0; i < 4; i++) asm volatile("mov.b32 %0, 0;\n" : "=r"(A[i]));
        if ((imp >> (wg * 4 + p)) & 1) {
          select_rows(A, sel, code + p * 0x800080u, p == 1 || p == 2);
          wgmma_fence();
          wgmma_rs(acc[p], A, w_desc(SB + SM_FIX));
          wgmma_commit();
        }
      };
      auto done = [&] {
        wgmma_wait<0>();
        keep_alive4(A, nv);
      };
      auto odd = [&](int i0, int i1) {
#pragma unroll
        for (int i = 0; i < 48; i++) {
          if (i < i0 || i >= i1) continue;
          if (i % 16 == 0) PIN_NEXT;
          UPD_ADD(acc[1][i], acc[3][i], 0.5f);
          UPD_ADD(acc[3][i], acc[1][i], 2.0f / 15.0f);
        }
      };
#pragma unroll
      for (int i = 0; i < 48; i++) {
        if (i % 8 == 0) PIN_NEXT;
        if (i == 24 && !wg) mbar_wait(bars + (B_VF + 5) * 8);
        UPD_ADD(acc[2][i], acc[3][i], 1.0f);
        UPD_MUL(acc[3][i], acc[2][i], -2.0f);
        UPD_ADD(acc[2][i], acc[0][i], 0.5f);
        UPD_ADD(acc[0][i], acc[2][i], 2.0f / 15.0f);
      }
      const uint32_t stg = sbase + warp * 1024, stb = bars + (B_ST + wg * 4) * 8;
      const uint32_t sa = stg + (lane & 15) * 64 + (((lane >> 4) ^ ((lane >> 1) & 3)) << 4);
      uint32_t pk[24];
      auto put = [&](int i, int jp) { stsm4(((sa + guard + w_stg(wg, i)) ^ ((jp & 1) * 32)) + (jp >> 1) * 4096, pk + jp * 4); };
      auto row = [&](int i, int g0, int g1) {
#pragma unroll
        for (int k = g0 * 4; k < g1 * 4; k++) pk[k] = pack2(acc[i][k * 2] * (8.0f / 15.0f), acc[i][k * 2 + 1] * (8.0f / 15.0f));
        PIN_NEXT;
#pragma unroll
        for (int g = g0; g < g1; g++) put(i, g);
      };
      corr(2);
      odd(0, 16);
      done();
      acc_fence(acc[2]);
      row(2, 0, 6);
      corr(0);
      odd(16, 48);
      publish(stb + 16, lane);
      done();
      corr(1);
      auto row1 = [&](int n) {
        if (n == 1) {
          keep_alive4(A, nv);
          acc_fence(acc[1]);
        }
        if (n == 2) mbar_wait(bars + (wg ? B_SR : B_RD) * 8);
        if (n >= 2 && n < 8) row(1, n - 2, n - 1);
        if (n == 9) publish(stb + 8, lane);
      };
      stage(acc[0], 12, w_slot(12), 10, 1, [&](int j) { row1(j); }, true, false);
      stage(acc[0], 13, w_slot(13), 8, 1, [&](int j) { row1(6 + j); });
      stage(acc[0], 14, w_slot(14), 12, 1, [](int) {});
      corr(3);
      guard |= gnext;
      auto row0 = [&](int n) {
        if (n == 2) {
          if (wg) mbar_wait(bars + B_WL * 8);
          acc_fence(acc[0]);
#pragma unroll
          for (int i = 0; i < 24; i++) pk[i] = pack2(acc[0][i * 2], acc[0][i * 2 + 1]);
        }
        if (n >= 2 && n < 5) {
          put(0, n * 2 - 4);
          put(0, n * 2 - 3);
        }
        if (n == 6) publish(stb, lane);
      };
      stage(acc[3], 15, w_slot(15), 11, 1, [&](int j) {
        if (j == 1) keep_alive4(A, nv);
        row0(j);
      });
      stage(acc[3], 16, w_slot(16), 9, 1, [&](int j) { row0(6 + j); }, false);
      stage(acc[3], 17, w_slot(17), 13, 1, [](int) {}, false);
      if (!wg) mbar_wait(bars + (B_SR + 1) * 8);
      wgmma_wait<0>();
      acc_fence(acc[3]);
      stage_slab(acc[3], stg + w_stg(wg, 3), lane);
      publish(stb + 24, lane);
      mbar_wait(bars + B_RD * 8);
      if (lds32(bars + O_CNT) > NREC || imp >= 0x10000u) {
        ntiles = 4;
        tile0 = (x0 >> 3) + wg + (y0 << 5);
        tstep = 0x100;
      }
    } else if (strip) {
      const uint32_t tab = sbase + SM_GT + wid * 1152;
      {
        const int r = (warp & 1) * 4 + (lane & 3), c = lane >> 2, pu = wid * 4 + (lane & 3), pv = x0 + c;
        const uint32_t oa = sbase + SM_GO + (wid >> 1) * 2304 + (left ? c * 8 + r : r * 8 + c) * 36, swap = left ? 0x3210u : 0x1032u;
        uint32_t bad = 0;
        mbar_wait(bars + B_OG * 8);
#pragma unroll 1
        for (int tv = 0; tv < 3; tv++) {
          const uint32_t base = pack2((float)(pv + tv - 1), (float)pu);
#pragma unroll
          for (int tu = 0; tu < 3; tu++) {
            const int tap = left ? tv * 3 + tu : tu * 3 + tv;
            const uint32_t gp = hadd2(base, tap_delta(1, tu));
            uint32_t d = hsub2(clip2(hadd2(gp, prmt(lds32(oa + tap * 4), 0, swap))), clip2(gp));
            const bool out = tu == 0 && pu == 0, off = strip_off(d, out);
            bad |= off ? 1u << tap : 0u;
            d = out ? 0x3f800000u : off ? 0u : d & 0xffff0000u;
            sts32(tab + tv * 384 + tu * 128 + lane * 4, d | ((int)d < 0 ? 0x7654u : 0x3210u));
          }
        }
        if (bad && pv >= 34) push_taps(bars, strip_key(pu, pv, left), bad, offs);
        __syncwarp();
        arrive_if(lane == 0 ? bars + B_SG * 8 : 0u);
      }
      wgmma_fence();
      wgmma_def(acc[1], w_desc(SB), never);
      wgmma_def(acc[0], w_desc(SB), never);
      wgmma_commit();
      wgmma_wait<0>();
      uint32_t la[3];
#pragma unroll
      for (int tv = 0; tv < 3; tv++) {
        const int p = (warp * 4 + ((lane >> 3) & 1)) * 10 + min((lane & 7) + tv, IW - x0);
        la[tv] = sbase + wg * GWIN + p * 64 + ((((lane >> 4) ^ (p >> 1)) & 3) << 4);
      }
      uint32_t D[2][8][2], A[3][8], dl[3][4];
#pragma unroll
      for (int i = 0; i < 6; i++) ldsm4(A[0] + i * 4, tab);
#pragma unroll
      for (int tu = 0; tu < 3; tu++) lds128(dl[tu], tab + tu * 128 + (lane >> 2) * 16);
      auto fetch = [&](int b, uint32_t a) {
#pragma unroll
        for (int i = 0; i < 4; i++) ldsm4(D[b][2 * i][0], D[b][2 * i + 1][0], D[b][2 * i][1], D[b][2 * i + 1][1], (a ^ (((i + b) & 1) * 32)) + i * 2 * GROW);
      };
      mbar_wait(bars + (B_XF + wg * 3) * 8);
      fetch(0, la[0]);
      int tn = 1;
#pragma unroll 1
      for (int st = 0; st < 9; st++) {
        const uint64_t bd = w_desc(SB + SM_GW) + (st < 7 ? st : st - 7) * (STAGE >> 4);
        mbar_wait(bars + (B_XF + wg * 3 + (st >= 5 ? 2 : st >= 2)) * 8);
        mbar_wait(bars + (B_WF + st) * 8);
#pragma unroll
        for (int kh = 0; kh < 2; kh++) {
          fetch(kh ^ 1, la[kh]);
          uint32_t E[7][2];
#pragma unroll
          for (int tu = 0; tu < 3; tu++) {
            wgmma_wait<2>();
            keep_alive8(A[tu], nv);
            if (kh == 1 && tu == 0) arrive_if((st == 1 || st == 2) && lane < 2 ? we_addr + st * 8 - 8 : 0u);
#pragma unroll
            for (int i = 0; i < 8; i++) {
              const int r = (i >> 2) * 2 + (i & 1), h = (i >> 1) & 1;
              if (tu == 0 && r == 0) E[0][h] = hsub2(D[kh][1][h], D[kh][0][h]);
              if (tu == 0 || r == 3) E[r + tu + 1][h] = hsub2(D[kh][r + tu + 2][h], D[kh][r + tu + 1][h]);
              A[tu][i] = hfma2_h(dl[tu][r], 1, prmt(E[r + tu + 1][h], E[r + tu][h], dl[tu][r]), D[kh][r + tu + 1][h]);
              if ((i & 3) == 3) {
                wgmma_fence();
                wgmma_rs(acc[i >> 2], A[tu] + (i & 4), bd + tu * WTAP + kh * WHALF, kh + tu ? 1 : st);
              }
            }
            wgmma_commit();
            if (kh) lds128(dl[tu], tab + tn * 384 + tu * 128 + (lane >> 2) * 16);
          }
        }
        const uint32_t l0 = la[0] + (st < 6 ? GSLICE : 0);
        la[0] = la[1];
        la[1] = la[2];
        la[2] = l0;
        tn = tn == 2 ? 0 : tn + 1;
      }
      mbar_wait(bars + B_IM * 8);
      mbar_wait(bars + B_SG * 8);
      uint32_t n0, imp, sel[2];
      lds64(n0, imp, bars + O_CNT);
      lds64(sel[0], sel[1], bars + O_SEL + (lane & 3) * 8);
      wgmma_wait<0>();
#pragma unroll
      for (int i = 0; i < 3; i++) keep_alive8(A[i], nv);
      if (__any_sync(0xffffffffu, (imp >> (wg * 4)) & 1)) {
        const uint32_t code = (wg * 512 + warp * 32 + (lane >> 2) + 0x4000u) * 0x10001u;
        select_rows(A[0], sel, code, false);
        select_rows(A[0] + 4, sel, code + 0x100010u, false);
        wgmma_fence();
        wgmma_rs(acc[0], A[0], w_desc(SB + SM_FIX));
        wgmma_rs(acc[1], A[0] + 4, w_desc(SB + SM_FIX));
        wgmma_commit();
        wgmma_wait<0>();
        keep_alive8(A[0], nv);
      }
      if (__any_sync(0xffffffffu, n0 > NREC || imp >= 0x10000u)) {
        mbar_wait(bars + B_RD * 8);
        ntiles = 2;
        tile0 = left ? wg * 2 + (x0 << 5) : (x0 >> 3) + (wg << 9);
        tstep = left ? 1 : 0x100;
      }
      acc_fence(acc[0]);
      acc_fence(acc[1]);
      bar_sync(1 + wg, 128);
      const uint32_t stg = sbase + wg * GWIN + warp * 2048;
      stage_slab<8192>(acc[0], stg, lane);
      stage_slab<8192>(acc[1], stg + 1024, lane);
      publish(bars + (B_ST + wg * 4) * 8, lane);
    } else {
      ntiles = !wg || cta >= -4;
      tile0 = corner_tile(wg);
      if (!ntiles) {
        arrive_if(lane == 0 ? bars + B_SG * 8 : 0u);
        if (own) {
          const uint32_t key = src < 7 ? wino_key(oy, ox) : strip_key(along, 32 + (t & 1), !lf);
          const uint32_t base = pack2((float)oy, (float)ox), swap = lf ? 0x3210u : 0x1032u, lim = src < 7 ? 0u : 0x3f00u;
          const uint32_t lim0 = along ? lim : 0u, limy = lf ? lim0 : lim, limx = lf ? lim : lim0;
          uint32_t bad = 0;
#pragma unroll
          for (int m = 0; m < 9; m++) {
            const uint32_t gp = hadd2(base, tap_delta(m / 3, m % 3));
            o2[m] = clip2(hadd2(gp, o2[m]));
            bad |= (prmt(hsub2(o2[m], clip2(gp)), 0, swap) & 0x7fff7fffu) > (m == 0 ? lim0 : m < 3 ? limy : m % 3 == 0 ? limx : lim) ? 1u << m : 0u;
          }
#pragma unroll 1
          for (; bad; bad &= bad - 1) {
            const int m = __ffs(bad) - 1;
            uint32_t pos = o2[0];
#pragma unroll
            for (int i = 1; i < 9; i++) pos = m == i ? o2[i] : pos;
            push_record(bars, key | (m << 16), pos);
          }
        }
        bar_sync(2, 128);
        const int n = __shfl_sync(0xffffffffu, lds32(bars + O_CNT), 0);
        if (n && n <= NREC) {
          const uint32_t tmp = sbase + SM_CX + CWIN;
#pragma unroll 1
          for (int i = t; i < n * 12; i += 128) {
            const int r = (i * 171) >> 11;
            uint32_t key, pos, v[4];
            lds64(key, pos, bars + O_REC + r * 8);
            delta(v, key, pos, reinterpret_cast<const uint4*>(x), i - r * 12);
            sts128(tmp + (r + i) * 16, v);
          }
          if (warp == 3) {
#pragma unroll 1
            for (int st = 0; st < 9; st++) mbar_wait(bars + (B_WF + st) * 8);
          }
          bar_sync(2, 128);
          const int r0 = warp ? 99 : lane >> 2;
          const uint32_t k0 = lds32(bars + O_REC + (lane >> 2) * 8), k1 = lds32(bars + O_REC + 64 + (lane >> 2) * 8);
          const uint32_t t0 = r0 < n ? (k0 >> 16) & 15 : 15, t1 = r0 + 8 < n ? (k1 >> 16) & 15 : 15;
          const uint32_t taps = __reduce_or_sync(0xffffffffu, lane < n ? 1u << ((lds32(bars + O_REC + (lane & 15) * 8) >> 16) & 15) : 0u);
          uint32_t D[6][4];
#pragma unroll
          for (int k = 0; k < 6; k++) ldsm4(D[k], tmp + (lane & 15) * 208 + (lane >> 4) * 16 + k * 32);
      wgmma_fence();
      wgmma_def(acc[0], w_desc(SB), never);
      wgmma_commit();
      wgmma_wait<0>();
#pragma unroll 1
          for (uint32_t m = taps; m; m &= m - 1) {
            const uint32_t tap = __ffs(m) - 1, ki = (tap * 11) >> 5;
            uint32_t A[6][4];
#pragma unroll
            for (int k = 0; k < 6; k++) {
#pragma unroll
              for (int i = 0; i < 4; i++) A[k][i] = (i & 1 ? t1 : t0) == tap ? D[k][i] : 0u;
            }
            wgmma_fence();
#pragma unroll
            for (int k = 0; k < 6; k++)
              wgmma_rs(acc[0], A[k], w_desc(SB) + ((k >> 1) * 3 + ki) * (STAGE >> 4) + (tap - ki * 3) * WTAP + (k & 1) * WHALF, k ? 1 : m ^ taps);
            wgmma_commit();
            wgmma_wait<0>();
#pragma unroll
            for (int k = 0; k < 3; k++) keep_alive8(A[2 * k], nv);
          }
          acc_fence(acc[0]);
          if (!warp) {
            uint32_t* dst = reinterpret_cast<uint32_t*>(scr->fix) + src * 768 + (lane >> 2) * 16 + (lane & 3);
#pragma unroll
            for (int j = 0; j < 24; j++) dst[(j >> 3) * 256 + (j & 1) * 128 + ((((j >> 1) ^ (lane >> 3)) & 3) << 2)] = pack2(acc[0][j * 2], acc[0][j * 2 + 1]);
          }
        }
        if (!warp) {
          __threadfence();
          __syncwarp();
          if (lane < NREC)
            asm volatile("st.relaxed.gpu.global.v2.u32 [%0], {%1, %2};\n" ::"l"(scr->key + src * NREC + lane), "r"(lds32(bars + O_REC + lane * 8)),
                         "r"((tag << 8) | min(n, 99)) : "memory");
          if (lane == 0) scr->launch[blockIdx.x] = tag;
        }
      }
    }
    if (ntiles) {
      const uint32_t winb = sbase + SM_CX + wg * CWIN, tab = sbase + SM_CT + wid * 1152;
      const uint32_t ck = (uint32_t)(lane >> 4) << 4, again = tstep != 0;
      if (tstep) {
        bar_sync(3, 256);
        if (wid == 0 && one) {
#pragma unroll 1
          for (int st = 0; st < 9; st++) load_cw(st);
        }
        __syncwarp();
      }
#pragma unroll 1
      for (int n = 0; n < ntiles; n++) {
        const uint32_t tl = tile0 + n * tstep;
        const int wx0 = (int)(tl & 255) * 8 - 2, wy0 = (int)(tl >> 8) * 8 - 2;
        if (tstep && warp == 0 && one) {
#pragma unroll 1
          for (int g = 0; g < 3; g++) load_cx(wg, g, tl);
        }
        __syncwarp();
        uint32_t mout = 0, need = 0, of[5];
        {
          const int ph = wy0 + 2 + 2 * warp + ((lane >> 3) & 1), pw = wx0 + 2 + (lane & 7);
          if (tstep) {
#pragma unroll
            for (int k = 0; k < 5; k++) of[k] = __ldg(offs + (ph * IW + pw) * 9 + min((lane >> 4) + 2 * k, 8));
          } else {
            mbar_wait(bars + B_OG * 8);
#pragma unroll
            for (int k = 0; k < 5; k++) of[k] = lds32(winb + 2 * CSLICE + (warp * 16 + (lane & 15)) * 36 + min((lane >> 4) + 2 * k, 8) * 4);
          }
#pragma unroll 1
          for (int m = lane >> 4; m < 9; m += 2) {
            const int ki = (m * 11) >> 5;
            const uint32_t pos = clip2(hadd2(pack2((float)(ph + ki - 1), (float)(pw + m - ki * 3 - 1)), of[0]));
#pragma unroll
            for (int k = 0; k < 4; k++) of[k] = of[k + 1];
            const uint32_t iy = (int)bf16lo(pos) - wy0, ix = (int)bf16hi(pos) - wx0, f = frac2(pos);
            mout |= max(iy, ix) > 10 ? 1u << m : 0u;
            need |= ((f >> 16 ? 1u : 0u) | (f & 0xffffu ? 0x200u : 0u) | (f >> 16 && f & 0xffffu ? 0x40000u : 0u)) << m;
            const uint32_t pp = (iy * 12 + ix) * 0x10001u + 0x10000u;
            sts32(tab + m * 64 + (lane & 7) * 8 + ((lane >> 1) & 4), f);
            sts32(tab + 576 + m * 64 + (lane & 15) * 4, pp * 64 + ((pp << 3) & 0x300030u));
            of[4] = pos;
          }
          mout = __reduce_or_sync(0xffffffffu, mout);
          need = __reduce_or_sync(0xffffffffu, need);
          arrive_if(lane == 0 && !tstep ? bars + B_SG * 8 : 0u);
        }
        uint32_t outside;
        asm volatile("{\n.reg .pred p, q;\nsetp.ne.u32 p, %1, 0;\nbarrier.red.or.pred q, %2, 128, p;\nselp.u32 %0, 1, 0, q;\n}\n"
                     : "=r"(outside) : "r"(mout), "r"(1 + wg) : "memory");
        outside = __shfl_sync(0xffffffffu, outside, 0);
        wgmma_fence();
        wgmma_def(acc[0], w_desc(SB), never);
        wgmma_commit();
        wgmma_wait<0>();
        if (!outside) {
          uint32_t T[3][4], C[2][3][4];
#pragma unroll
          for (int i = 0; i < 9; i++) ldsm4(i < 3 ? T[i] : C[0][i - 3], tab);
          uint32_t ad[4];
          auto fetch = [&](int k, uint32_t e, uint32_t slice, uint32_t nd) {
            if (!(k & 1)) {
              ad[0] = (e & 0xffffu) + slice;
              ad[1] = (e >> 16) + slice;
              ad[2] = ad[0] ^ 32;
              ad[3] = ad[1] ^ 32;
            }
            ldsm4_if(T[k % 3], ad[(k & 1) * 2], never ^ 1);
            ldsm4_if(C[k & 1][0], ad[(k & 1) * 2 + 1], nd & 1);
            ldsm4_if(C[k & 1][1], ad[2 - (k & 1) * 2] + CROW, nd & 0x200u);
            ldsm4_if(C[k & 1][2], ad[3 - (k & 1) * 2] + CROW, nd & 0x40000u);
          };
          uint32_t ent[3], slice = winb;
          const uint32_t ck2 = ck * 0x10001u;
          mbar_wait(bars + (B_XF + wg * 3) * 8, (n + again) & 1);
          fetch(0, lds32(tab + 576 + (lane & 15) * 4) ^ ck2, slice, need);
          int ki = 0, g = 0;
#pragma unroll 1
          for (int st = 0; st < 9; st++) {
            const uint64_t bd = w_desc(SB) + st * (STAGE >> 4);
            const int kn = ki == 2 ? 0 : ki + 1;
            uint32_t cf[3][4];
#pragma unroll
            for (int j = 0; j < 3; j++) {
              uint32_t wA, wB;
              lds64(wA, wB, tab + (ki * 3 + j) * 64 + (lane >> 2) * 8);
              ent[j] = lds32(tab + 576 + (j < 2 ? ki * 3 + j + 1 : kn * 3) * 64 + (lane & 15) * 4) ^ ck2;
              coefs(wA, cf[j][0], cf[j][1]);
              coefs(wB, cf[j][2], cf[j][3]);
            }
            if (kn == 0 && g < 2) mbar_wait(bars + (B_XF + wg * 3 + g + 1) * 8, (n + again) & 1);
            mbar_wait(bars + (B_WF + st) * 8, again);
#pragma unroll
            for (int k = 0; k < 6; k++) {
              wgmma_wait<1>();
              if (k == 5 && kn == 0 && g < 2) {
                g++;
                slice += CSLICE;
              }
              fetch(k + 1, ent[k >> 1], slice, need >> (k < 5 ? ki * 3 + ((k + 1) >> 1) : kn * 3));
              blend4(T[k % 3], C[k & 1][0], C[k & 1][1], C[k & 1][2], cf[k >> 1][0], cf[k >> 1][1], cf[k >> 1][2], cf[k >> 1][3]);
              wgmma_fence();
              wgmma_rs(acc[0], T[k % 3], bd + (k >> 1) * WTAP + (k & 1) * WHALF, k ? 1 : st);
              wgmma_commit();
            }
            ki = kn;
          }
          wgmma_wait<0>();
          keep_alive8(T[0], nv);
          keep_alive8(T[1], nv);
        } else {
#pragma unroll
          for (int k = 0; k < 5; k++) {
            const int m = 2 * k - (lane >> 4);
            if (m >= 0) sts32(tab + m * 64 + (lane & 7) * 8 + ((lane >> 1) & 4), of[k]);
          }
          __syncwarp();
          uint32_t buf[2][8];
#pragma unroll
          for (int i = 0; i < 16; i++) buf[0][i] = nv;
          const uint32_t tmp = tab + 576 + lane * 16;
          int tap = 0, g = 0;
#pragma unroll 1
          for (int d = 0;; d += 2) {
#pragma unroll
            for (int b = 0; b < 2; b++) {
              const int k = d + b, q = (k * 11) >> 5;
              if (k == 27) goto tile_done;
              mbar_wait(bars + (B_XF + wg * 3 + g) * 8, (n + again) & 1);
              mbar_wait(bars + (B_WF + q) * 8, again);
              const uint32_t pos = lds32(tab + tap * 64 + (lane & 7) * 8 + ((lane >> 1) & 4));
              const int gy = (int)bf16lo(pos), gx = (int)bf16hi(pos);
              uint32_t T[8];
              if (!((mout >> tap) & 1)) {
                uint32_t wA, wB, pA0, pA1, pB0, pB1, G[4], H[4], K[4];
                lds64(wA, wB, tab + tap * 64 + (lane >> 2) * 8);
                const uint32_t slice = winb + g * CSLICE;
                const uint32_t p = (gy - wy0) * 12 + gx - wx0, p1 = p + 1;
                const uint32_t a00 = slice + p * 64 + (((p << 3) & 0x30) ^ ck), a01 = slice + p1 * 64 + (((p1 << 3) & 0x30) ^ ck);
                coefs(frac2(wA), pA0, pA1);
                coefs(frac2(wB), pB0, pB1);
#pragma unroll
                for (int hf = 0; hf < 2; hf++) {
                  ldsm4(T + hf * 4, a00 ^ (hf * 32));
                  ldsm4(G, a01 ^ (hf * 32));
                  ldsm4(H, (a00 + CROW) ^ (hf * 32) ^ 32);
                  ldsm4(K, (a01 + CROW) ^ (hf * 32) ^ 32);
                  blend4(T + hf * 4, G, H, K, pA0, pA1, pB0, pB1);
                }
              } else {
                uint32_t q0, q1;
                coefs(frac2(pos), q0, q1);
                const int sx = gx < IW - 1 ? IC / 8 : 0, sy = gy < IH - 1 ? IW * IC / 8 : 0;
                const uint4* pc = reinterpret_cast<const uint4*>(x) + (gy * IW + gx) * (IC / 8) + g * 4 + (lane >> 4);
#pragma unroll
                for (int hf = 0; hf < 2; hf++) {
                  uint4 v[4];
                  v[0] = __ldg(pc + hf * 2);
                  v[1] = __ldg(pc + hf * 2 + sx);
                  v[2] = __ldg(pc + hf * 2 + sy);
                  v[3] = __ldg(pc + hf * 2 + sy + sx);
                  blend4(&v[0].x, &v[1].x, &v[2].x, &v[3].x, q0, q1, q0, q1);
                  __syncwarp();
                  sts128(tmp, &v[0].x);
                  __syncwarp();
                  ldsm4(T + hf * 4, tmp);
                }
              }
              wgmma_wait<1>();
              keep_alive8(buf[b], nv);
#pragma unroll
              for (int i = 0; i < 8; i++) asm volatile("xor.b32 %0, %1, %2;\n" : "=r"(buf[b][i]) : "r"(T[i]), "r"(nv));
              const uint64_t bd = w_desc(SB) + q * (STAGE >> 4) + (k - q * 3) * WTAP;
              wgmma_fence();
              wgmma_rs(acc[0], buf[b], bd, k);
              wgmma_rs(acc[0], buf[b] + 4, bd + WHALF);
              wgmma_commit();
              if (++tap == 9) {
                tap = 0;
                g++;
              }
            }
          }
        tile_done:
          wgmma_wait<0>();
          keep_alive8(buf[0], nv);
          keep_alive8(buf[1], nv);
        }
        acc_fence(acc[0]);
        bar_sync(1 + wg, 128);
        stage_slab(acc[0], winb + warp * 1024, lane);
        fence_async();
        bar_sync(1 + wg, 128);
        if (warp == 0 && one) {
          tma_store(&tm.out[3], winb, wx0 + 2, wy0 + 2, 0);
          asm volatile("cp.async.bulk.wait_group.read 0;\n" ::: "memory");
        }
      }
    }
  } else if (wid < 12) {
    asm volatile("setmaxnreg.dec.sync.aligned.u32 40;\n");
    if (prep) {
      const int lane = lane_now();
      uint32_t u[4][4];
      weights4<true>(&g[0].x, &g[1].x, &g[2].x, u);
      const uint8_t* udst = scr->u + ((cta >> 2) & 1) * (4 * STAGE) + (cta & 2) * (STAGE / 4) + ((cta - NW) >> 3) * 3072 + (wid - 8) * 1024 +
                            (cta & 1) * 512 + (lane >> 2) * 64 + (((lane ^ (lane >> 3)) & 3) << 4);
#pragma unroll
      for (int k = 0; k < 4; k++)
        asm volatile("st.relaxed.gpu.global.v4.b32 [%0], {%1, %2, %3, %4};\n" ::"l"(udst + k * STAGE), "r"(u[k][0]), "r"(u[k][1]), "r"(u[k][2]), "r"(u[k][3]) : "memory");
      uint32_t chk = 0;
#pragma unroll
      for (int k = 0; k < 4; k++) {
        uint32_t v;
        asm volatile("ld.relaxed.gpu.global.b32 %0, [%1];\n" : "=r"(v) : "l"(udst + k * STAGE) : "memory");
        chk |= v;
      }
      chk = __reduce_or_sync(0xffffffffu, chk & never);
      if (one) asm volatile("red.relaxed.gpu.global.add.u32 [%0], %1;\n" ::"l"(scr->cnt), "r"(chk + 1) : "memory");
    }
    asm volatile("barrier.cluster.wait.acquire.aligned;\n" ::: "memory");
    const int w = wid - 8, lane = lane_now();
    uint32_t asked = 1;
    if (wino) {
      bar_sync(12, 384);
      arrive_if(one ? bars + (B_WF + w) * 8 : 0u);
      const int hi = w >> 1, ty = (w & 1) * 4 + (lane >> 4);
      const bool bottom = y0 + 4 * ty + 12 == IH;
      uint32_t d[2][6][2];
      auto fetch = [&](int u, uint32_t src, bool low = false) {
#pragma unroll
        for (int r = 0; r < 5; r++) lds64(d[u][r][0], d[u][r][1], src + u * 1024 + r * 128);
        lds64(d[u][5][0], d[u][5][1], src + u * 1024 + ((u || low) && bottom ? 4 * 128 : 5 * 128));
      };
      uint32_t src = sbase + SM_R + hi * PIECE + ty * 512 + (lane & 15) * 8;
      uint32_t v0 = sbase + ty * VROW + hi * 128 + (lane & 8) * 8 + (lane & 1) * 8 + ((((lane >> 1) ^ (ty + hi)) & 3) << 4);
      auto vl = [&] { return (v0 ^ (hi ? (lane_now() & 16 ? 16 : 48) : 0)) + 1024 + hi * (2 * VROW - 128); };
      mbar_wait(bars + (B_XF + 2) * 8);
      fetch(0, src + 4 * VSLOT - SM_R + (4 - hi) * PIECE + hi * 1024, hi);
      transform6<2>(d[0], vl() - 512, 10 * VSLOT);
      publish(bars + B_V0 * 8, !one);
      mbar_wait(bars + B_V0 * 8);
      mbar_wait(bars + (B_VF + 1) * 8);
      v0 += 4 * VSLOT;
#pragma unroll 1
      for (int s = 0; s < 2; s++) {
        const uint32_t xf = bars + (B_XF + 5 + s * 5) * 8, off0 = s ? 12 * VSLOT : 4 * VSLOT;
        if (s) mbar_wait(bars + B_VE * 8);
        mbar_wait(xf);
        fetch(0, src);
#pragma unroll 1
        for (int jj = 0; jj < 4; jj += 2) {
          asm volatile("" : "+r"(src), "+r"(v0));
#pragma unroll
          for (int e = 0; e < 2; e++) {
            const int j = jj + e;
            const uint32_t ready = mbar_poll(xf + j * 8 + 8);
            fetch(1, src + e * 2 * PIECE);
            transform6<2>(d[0], (v0 ^ e * 32) + e * 256, off0);
            if (!ready) mbar_wait(xf + j * 8 + 8);
            fetch(0, (src + ((e + 1) * 2 * PIECE - (j == 3 ? hi * (PIECE - 1024) : 0))) & (j == 3 && x0 + 16 == IW ? ~64u : ~0u), j == 3 && hi);
            transform6<2>(d[1], (v0 ^ (e ^ 1) * 32) + e * 256 + 2 * VROW, off0);
            __syncwarp();
            arrive_if(one && (!s || j == 2) ? bars + (B_RE + j + s * 3) * 8 : 0u);
            if (j + hi == 2) publish(bars + (B_VF + 2 + s * 2) * 8, !one);
          }
          src += 4 * PIECE;
          v0 += 512;
        }
        transform6<2>(d[0], vl() - 1024, off0);
        publish(bars + (B_VF + 3 + s * 2) * 8, !one);
        arrive_if(one && !s ? bars + (B_RE + 4) * 8 : 0u);
        v0 -= 4 * VSLOT + 1024;
        src -= 8 * PIECE;
      }
      mbar_wait(bars + B_OF * 8);
      uint32_t mx = 0;
#pragma unroll
      for (int h = 0; h < 2; h++) {
        uint32_t v[6][4];
#pragma unroll
        for (int k = 0; k < 6 - 3 * h; k++) lds128(v[k], sbase + SM_R + w * 4608 + (h * 6 + k) * 512 + lane * 16);
#pragma unroll
        for (int k = 0; k < 6 - 3 * h; k++) mx = absmax2(mx, absmax2(absmax2(v[k][0], v[k][1]), absmax2(v[k][2], v[k][3])));
      }
      const uint32_t lim = (pack2((float)max(y0, 34) - 1.5f, (float)max(x0, 34) - 1.5f) & 0x7f807f80u) - 0x04000400u;
      uint32_t who = __ballot_sync(0xffffffffu, (mx & 0x7fffu) >= (lim & 0xffffu) || (mx & 0x7fff0000u) >= (lim & 0xffff0000u));
      asm volatile("{\n.reg .pred p, q;\nsetp.ne.u32 p, %1, 0;\nbarrier.red.or.pred q, 4, 128, p;\nselp.u32 %0, 1, 0, q;\n}\n"
                   : "=r"(asked) : "r"(who) : "memory");
      arrive_if(!asked && w == 0 && one ? bars + B_RD * 8 : 0u);
#pragma unroll 1
      for (; who; who &= who - 1) {
#pragma unroll 1
        for (int k = lane; k < 64; k += 32) {
          const int wd = (k >> 2) * 128 + (__ffs(who) - 1) * 4 + (k & 3), c = (wd * 7282) >> 16, tap = wd - c * 9, ki = (tap * 11) >> 5;
          const int y = y0 + w * 8 + (c >> 4), xx = x0 + (c & 15);
          if (k < 36 && min(y, xx) >= 34) {
            const uint32_t gp = pack2((float)(y + ki - 1), (float)(xx + tap - ki * 3 - 1));
            const uint32_t pos = clip2(hadd2(gp, lds32(sbase + SM_R + w * 4608 + wd * 4)));
            if (pos != clip2(gp)) push_record(bars, wino_key(y, xx) | (tap << 16), pos);
          }
          __syncwarp();
        }
      }
      bar_sync(4, 128);
    }
    if (wino || strip) {
      if (strip) mbar_wait(bars + B_SG * 8);
      const uint32_t n0 = __shfl_sync(0xffffffffu, lds32(bars + O_CNT), 0);
      if (n0 <= NREC) fixup(bars, w, n0, reinterpret_cast<const uint4*>(x), wgt);
      if (w == 0) {
        arrive_if(one && asked ? bars + B_RD * 8 : 0u);
        mbar_wait(bars + B_IM * 8);
        if (one) atomicAdd(scr->launch + blockIdx.x, 1);
      }
    }
  } else {
    asm volatile("setmaxnreg.dec.sync.aligned.u32 24;\n");
    asm volatile("barrier.cluster.wait.acquire.aligned;\n" ::: "memory");
    auto wait_all = [&](uint32_t dt) {
      while (__shfl_sync(0xffffffffu, clock32(), 0) - tstart < dt) __nanosleep(40);
    };
    if (wid == 15 && !wino) {
      const uint32_t dst = sbase + (strip ? SM_GW : 0) + (cta & 1) * (STAGE / 2);
      int g = 0, r = 0;
#pragma unroll 1
      for (int k = 0; k < 9; k++) {
        if (strip && k >= 7) mbar_wait(bars + (B_WE + k - 7) * 8);
        else wait_all(strip ? GW0 + k * GWS : CW0 + k * CWS);
        if (one) {
          mbar_expect_tx(bars + (B_WF + k) * 8, STAGE);
          tma_load_w(dst + (strip && k >= 7 ? k - 7 : k) * STAGE, &tm.w[left], bars + (B_WF + k) * 8, g + (cta & 1) * 16, left ? 0 : r, left ? r : 0, 3);
        }
        if (++r == 3) {
          r = 0;
          g += 32;
        }
      }
    }
    if (wid >= 13 && wid < 15 && !wino) {
      const int r = 14 - wid;
      const uint32_t tl = corner_tile(r);
#pragma unroll 1
      for (int g = 0; g < 3; g++) {
        if (g == 2) mbar_wait(bars + B_SG * 8);
        wait_all(strip ? (r ? GX1 : GX0) + g * GXS : CX0 + g * CXS);
        if (one && (strip || (g && (!r || cta >= -4))))
          tma_load_x(sbase + (strip ? r * GWIN + g * GSLICE : SM_CX + r * CWIN + g * CSLICE), &tm.x[strip ? 1 + left : 3],
                     bars + (B_XF + r * 3 + g) * 8, strip ? GSLICE : CSLICE, g * 32, strip ? x0 - 1 : (int)(tl & 255) * 8 - 2,
                     strip ? r * 16 - 2 : (int)(tl >> 8) * 8 - 2);
      }
    }
    if (wid == 15 && wino) {
      if (one) {
        wait_until(tstart, SDELAY);
#pragma unroll
        for (int j = 0; j < 2; j++) load_cols(1, j);
        wait_until(tstart, SDELAY + SDELAY2);
#pragma unroll
        for (int j = 2; j < 5; j++) load_cols(1, j);
        wait_until(tstart, PDELAY);
        asm volatile(
            "{\n.reg .pred p;\n.reg .u32 n, v;\nmov.u32 n, 0;\n"
            "W_%=:\n"
            "ld.relaxed.gpu.global.u32 v, [%0];\nsetp.ge.u32 p, v, 72;\n"
            "@p bra D_%=;\n"
            "add.u32 n, n, 1;\nsetp.lt.u32 p, n, 0x100000;\n@p bra W_%=;\ntrap;\n"
            "D_%=:\n}\n" ::"l"(scr->cnt)
            : "memory");
        asm volatile("fence.proxy.async.global;\n" ::: "memory");
        atomicInc(scr->cnt, 72 + NW - 1);
      }
      bar_sync(13, 32);
    }
    if (wid == 15) {
      if (wino) {
#pragma unroll 1
        for (int k = 0; k < 8; k++) {
          mbar_wait(bars + (B_WE + ((0x77654210u >> (4 * k)) & 15)) * 8);
          if (one)
            bulk_load_mc(sbase + (uint32_t)((w_slots(4, 1, 8) >> (8 * k)) & 255) * 1024 + (cta & 1) * (STAGE / 2),
                         scr->u + (k * 2 + (cta & 1)) * (STAGE / 2), STAGE / 2, bars + (B_WF + 4 + k) * 8);
        }
#pragma unroll
        for (int k = 0; k < 6; k++) {
          if (k > 0 && k < 5) mbar_wait(bars + (B_WE + min(7 + k, 11)) * 8);
          if (one)
            tma_load_w(sbase + (uint32_t)((w_slots(12, 1, 6) >> (8 * k)) & 255) * 1024 + (cta & 1) * (STAGE / 2), &tm.w[1],
                       bars + (B_WF + 12 + k) * 8, (k < 3 ? k : k - 3) * 32 + (cta & 1) * 16, 0, k < 3 ? 0 : 2, 3);
        }
      }
    } else if (wid == 14) {
      if (one && wino) {
#pragma unroll
        for (int j = 0; j < 5; j++) {
          mbar_wait(bars + (B_RE + j) * 8);
          load_cols(2, j);
        }
      }
    } else if (wino || strip) {
      const int wg = wid - 12;
      if (one) {
        if (wino && wg) {
#pragma unroll 1
          for (int i = 4; i < 18; i++) mbar_expect_tx(bars + (B_WF + i) * 8, STAGE);
        } else if (wino) {
#pragma unroll 1
          for (int i = 0; i < 15; i++) mbar_expect_tx(bars + (B_XF + i) * 8, (0x4210 >> i) & 1 ? PIECE : 2 * PIECE);
        }
        asm volatile("prefetch.tensormap [%0];\n" ::"l"(reinterpret_cast<uint64_t>(&tm.out[wino ? 0 : 1 + left])) : "memory");
      }
      if (wino && !wg) {
        if (one) {
          wait_until(tstart, FDELAY);
          asm volatile("cp.async.bulk.prefetch.tensor.2d.L2.global [%0, {%1, %2}];\n" ::"l"(reinterpret_cast<uint64_t>(&tm.o[0])), "r"(x0 * 9), "r"(y0) : "memory");
          mbar_expect_tx(bars + B_OF * 8, 2 * VSLOT);
          mbar_wait(bars + B_R2 * 8);
          tma_load_o(sbase + SM_R, &tm.o[0], bars + B_OF * 8, x0, y0);
        }
        bar_sync(7, 32);
      }
      if (wg == wino) {
        bar_sync(6, 32);
        const int lane = lane_now();
        const uint32_t tag = scr->launch[blockIdx.x] + 1;
        uint32_t n = 0;
        if (x0 == 32 || (wino && y0 == 32)) {
          wait_all(IDELAY);
          const int src = !wino ? 7 : ry ? (ry + 7) >> 1 : (0xfea550u >> (2 * cta)) & 3;
          uint32_t key, v;
          asm volatile(
              "{\n.reg .pred p;\n.reg .u32 n, t;\nmov.u32 n, 0;\n"
              "W_%=:\n"
              "ld.acquire.gpu.global.v2.u32 {%0, %1}, [%2];\nxor.b32 t, %1, %3;\nsetp.lt.u32 p, t, 256;\nvote.sync.all.pred p, p, 0xffffffff;\n"
              "@p bra D_%=;\n"
              "nanosleep.u32 100;\nadd.u32 n, n, 1;\nsetp.lt.u32 p, n, 0x100000;\n@p bra W_%=;\ntrap;\n"
              "D_%=:\nfence.proxy.async.global;\n}\n"
              : "=r"(key), "=r"(v)
              : "l"(scr->key + src * NREC + (lane & 15)), "r"(tag << 8)
              : "memory");
          v &= 255;
          const uint32_t dy = (key & 255) - (wino ? y0 : left ? 32 : 0), dx = ((key >> 8) & 255) - (wino || !left ? x0 : 0);
          const bool mine = lane < v && dy < 32 && dx < (left ? 32 : 16);
          n = __reduce_or_sync(0xffffffffu, v > NREC ? 0x10000u : mine ? 1u << (key >> 27) : 0u);
          put_sel(bars, mine ? key : ~0u, lane);
          if (n && n < 256 && one) {
            asm volatile("mbarrier.expect_tx.relaxed.cta.shared::cta.b64 [%0], 3072;\n" ::"r"(bars + B_IM * 8) : "memory");
            asm volatile("cp.async.bulk.shared::cluster.global.mbarrier::complete_tx::bytes [%0], [%1], 3072, [%2];\n" ::"r"(sbase + SM_FIX),
                         "l"(scr->fix + src * 192), "r"(bars + B_IM * 8) : "memory");
          }
          __syncwarp();
        }
        if (lane == 0) sts32(bars + O_CNT + 4, n + (tag & never));
        __syncwarp();
        arrive_if(lane == 0 ? bars + B_IM * 8 : 0u);
      }
      mbar_wait(bars + B_IM * 8);
      mbar_wait(bars + B_RD * 8);
      uint32_t n0, imp;
      lds64(n0, imp, bars + O_CNT);
      if (__all_sync(0xffffffffu, n0 <= NREC && imp < 0x10000u)) {
        const int lane = lane_now();
        const uint32_t key = lane < n0 ? lds32(bars + O_REC + lane * 8) : ~0u;
        const CUtensorMap* map = &tm.out[wino ? 0 : 1 + left];
        const int c1 = x0 + (wino ? wg * 8 : 0), c3 = wino ? y0 >> 2 : 0;
#pragma unroll 1
        for (int i = wino ? 2 : 0;; i = (i - 1) & 3) {
          const uint32_t stg = sbase + (wino ? w_stg(wg, i) : wg * GWIN), sb = bars + (B_ST + wg * 4 + i) * 8;
          uint32_t mask = __ballot_sync(0xffffffffu, key >> 27 == wg * 4 + i);
          if (mask) {
#pragma unroll 1
            do {
              const uint32_t r = __ffs(mask) - 1, m = (__shfl_sync(0xffffffffu, key, r) >> 20) & 127, l = min(lane, 23);
              const uint32_t a = stg + (l >> 3) * (wino ? 4096 : 8192) + m * 64 + ((((l ^ m) >> 1) & 3) << 4) + (l & 1) * 8;
              uint32_t v[2], c[2];
              lds64(c[0], c[1], sbase + SM_FIX + 3072 + r * 192 + l * 8);
              mbar_wait(sb);
              lds64(v[0], v[1], a);
              v[0] = hadd2(v[0], c[0]);
              v[1] = hadd2(v[1], c[1]);
              sts64(a, v);
              mask &= mask - 1;
            } while (mask);
            fence_async();
            __syncwarp();
          }
          mbar_wait(sb);
          if (one) tma_store(map, stg, c1, wino ? i : wg * 16, c3);
          if (!wg && wino && i < 2) {
            asm volatile("cp.async.bulk.wait_group.read 1;\n" ::: "memory");
            arrive_if(one ? bars + (B_SR + 1 - i) * 8 : 0u);
          }
          if (i == 3 || !wino) break;
        }
        asm volatile("cp.async.bulk.wait_group.read 0;\n" ::: "memory");
      } else {
        arrive_if(one ? bars + (B_SR + wg) * 8 : 0u);
      }
    }
  }
}

typedef CUresult (*EncodeTiledFn)(CUtensorMap*, CUtensorMapDataType, cuuint32_t, void*, const cuuint64_t*,
                                  const cuuint64_t*, const cuuint32_t*, const cuuint32_t*, CUtensorMapInterleave,
                                  CUtensorMapSwizzle, CUtensorMapL2promotion, CUtensorMapFloatOOBfill);

}

extern "C" void kernel_launch(void* const* d_in, const int* in_sizes, int n_in, void* d_out, int out_size) {
  static EncodeTiledFn encode = nullptr;
  static void* scratch = nullptr;
  if (!encode) {
    cudaGetSymbolAddress(&scratch, g_scratch);
    void* fn = nullptr;
    cudaDriverEntryPointQueryResult qres;
    cudaGetDriverEntryPoint("cuTensorMapEncodeTiled", &fn, cudaEnableDefault, &qres);
    encode = (EncodeTiledFn)fn;
    cudaFuncSetAttribute(dcn_kernel, cudaFuncAttributeMaxDynamicSharedMemorySize, SMEM_BYTES);
  }
  Maps tm;
  const cuuint32_t es[5] = {1, 1, 1, 1, 1};
  constexpr cuuint64_t PX = IC * 2, ROW = IW * IC * 2;
  for (int i = 0; i < 4; i++) {
    const cuuint64_t dims[3] = {IC, IW, IH};
    const cuuint64_t strides[2] = {i == 2 ? ROW : PX, i == 2 ? PX : ROW};
    const cuuint32_t box[4][3] = {{32, 2, 34}, {32, 10, 20}, {32, 10, 20}, {32, 12, 12}};
    encode(&tm.x[i], CU_TENSOR_MAP_DATA_TYPE_BFLOAT16, 3, d_in[0], dims, strides, box[i], es, CU_TENSOR_MAP_INTERLEAVE_NONE,
           i ? CU_TENSOR_MAP_SWIZZLE_64B : CU_TENSOR_MAP_SWIZZLE_NONE, CU_TENSOR_MAP_L2_PROMOTION_NONE,
           CU_TENSOR_MAP_FLOAT_OOB_FILL_NONE);
  }
  {
    const cuuint64_t dims[4] = {IC, 2, IH, IW / 2 - 1};
    const cuuint64_t strides[3] = {PX, ROW, 2 * PX};
    const cuuint32_t box[4] = {32, 2, 34, 2};
    encode(&tm.x[4], CU_TENSOR_MAP_DATA_TYPE_BFLOAT16, 4, (char*)d_in[0] + PX, dims, strides, box, es, CU_TENSOR_MAP_INTERLEAVE_NONE,
           CU_TENSOR_MAP_SWIZZLE_NONE, CU_TENSOR_MAP_L2_PROMOTION_NONE, CU_TENSOR_MAP_FLOAT_OOB_FILL_NONE);
  }
  for (int i = 0; i < 2; i++) {
    const cuuint64_t dims[5] = {32, IC, 3, 3, 3};
    const cuuint64_t strides[4] = {IC * 2, 64, IC * IC * 2, 3 * IC * IC * 2};
    const cuuint32_t box[5] = {32, 16, 3, i ? 3u : 1u, i ? 1u : 3u};
    encode(&tm.w[i], CU_TENSOR_MAP_DATA_TYPE_BFLOAT16, 5, d_in[2], dims, strides, box, es, CU_TENSOR_MAP_INTERLEAVE_NONE,
           CU_TENSOR_MAP_SWIZZLE_64B, CU_TENSOR_MAP_L2_PROMOTION_L2_128B, CU_TENSOR_MAP_FLOAT_OOB_FILL_NONE);
  }
  for (int i = 0; i < 2; i++) {
    const cuuint64_t dims[2] = {IW * 9, IH};
    const cuuint64_t strides[1] = {IW * 36};
    const cuuint32_t box[2] = {i ? 72u : 144u, i ? 8u : 32u};
    encode(&tm.o[i], CU_TENSOR_MAP_DATA_TYPE_UINT32, 2, d_in[1], dims, strides, box, es, CU_TENSOR_MAP_INTERLEAVE_NONE,
           CU_TENSOR_MAP_SWIZZLE_NONE, CU_TENSOR_MAP_L2_PROMOTION_NONE, CU_TENSOR_MAP_FLOAT_OOB_FILL_NONE);
  }
  for (int i = 0; i < 4; i++) {
    const cuuint64_t dims[5] = {32, IW, i ? IH : 4u, i ? 1u : IH / 4, 3};
    const cuuint64_t strides[4] = {i == 2 ? ROW : PX, i == 2 ? PX : ROW, 4 * ROW, 64};
    const cuuint32_t box[5] = {32, 8, i == 3 ? 8u : i ? 16u : 1u, i ? 1u : 8u, 3};
    encode(&tm.out[i], CU_TENSOR_MAP_DATA_TYPE_BFLOAT16, 5, d_out, dims, strides, box, es, CU_TENSOR_MAP_INTERLEAVE_NONE,
           CU_TENSOR_MAP_SWIZZLE_64B, CU_TENSOR_MAP_L2_PROMOTION_NONE, CU_TENSOR_MAP_FLOAT_OOB_FILL_NONE);
  }
  dcn_kernel<<<GRID, NTHREADS, SMEM_BYTES>>>((const __nv_bfloat16*)d_in[0], (const uint32_t*)d_in[1], (const uint4*)d_in[2],
                                             (Scratch*)scratch, 0u, tm);
}
```

```cpp
#include <cuda_runtime.h>
#include <cuda.h>
#include <cuda_bf16.h>
#include <stdint.h>

namespace {

constexpr int IH = 224, IW = 224, IC = 96;
constexpr int GRID = 132, NC = 12, NW = 72, NG = 48;
constexpr int NTHREADS = 512;
constexpr int STAGE = 18432;
constexpr int WTAP = 3072 >> 4, WHALF = (STAGE / 2) >> 4;
constexpr uint32_t SB = 0x400;
constexpr int VROW = 18 * 64, VSLOT = 8 * VROW, PIECE = 34 * 128;
constexpr int SM_R = 14 * VSLOT, SM_WW = SM_R + 39936;
constexpr int GROW = 10 * 64, GSLICE = 20 * GROW, GWIN = 3 * GSLICE, SM_GW = 2 * GWIN, SM_GO = SM_GW + 7 * STAGE, SM_GT = SM_GO + 9216;
constexpr int CROW = 12 * 64, CSLICE = 12 * CROW, CWIN = 3 * CSLICE, SM_CX = 9 * STAGE, SM_CT = SM_CX + 2 * CWIN;
constexpr int SM_FIX = 224256, SM_BAR = 231168, SMEM_BYTES = 232448;
constexpr int B_XF = 0;
constexpr int B_OG = 7;
constexpr int B_WF = 16;
constexpr int B_IM = 34;
constexpr int B_OF = 35;
constexpr int B_SR = 36;
constexpr int B_RD = 39;
constexpr int B_W2 = 96;
constexpr int B_WE = 40;
constexpr int B_WL = 56;
constexpr int B_V0 = 57;
constexpr int B_SG = 58;
constexpr int B_VE = 59;
constexpr int B_ST = 64;
constexpr int B_VF = 71;
constexpr int B_RE = 80;
constexpr int B_R2 = 85;
constexpr int B_PP = 86;
constexpr int O_CNT = 776, O_REC = 784, O_SEL = 912;
constexpr int NREC = 16;
constexpr uint32_t SDELAY = 3000, SDELAY2 = 500, PDELAY = 5200, FDELAY = 9500, IDELAY = 8000;
constexpr uint32_t GX0 = 1500, GXS = 2000, GXE = 1500, GX1 = 4000, GXS1 = 3700, GW0 = 1600, GWS = 850;
constexpr uint32_t CX0 = 1000, CXS = 2200, CW0 = 1000, CWS = 300;

struct Scratch {
  uint8_t u[8 * STAGE];
  uint4 fix[8 * NREC * 12];
  uint2 key[8 * NREC];
  uint32_t cnt[32];
  uint32_t launch[160];
};
__device__ __align__(128) Scratch g_scratch;

__device__ __forceinline__ float bf16lo(uint32_t v) { return __uint_as_float(v << 16); }
__device__ __forceinline__ float bf16hi(uint32_t v) { return __uint_as_float(v & 0xffff0000u); }
__device__ __forceinline__ uint32_t smem_u32(const void* p) { return (uint32_t)__cvta_generic_to_shared(p); }
__device__ __forceinline__ void mbar_init(uint32_t bar, uint32_t count) {
  asm volatile("mbarrier.init.shared::cta.b64 [%0], %1;\n" ::"r"(bar), "r"(count) : "memory");
}
__device__ __forceinline__ void mbar_expect_tx(uint32_t bar, uint32_t bytes) {
  asm volatile("mbarrier.arrive.expect_tx.shared::cta.b64 _, [%0], %1;\n" ::"r"(bar), "r"(bytes) : "memory");
}
__device__ __forceinline__ void mbar_wait(uint32_t bar, uint32_t parity = 0) {
  asm volatile(
      "{\n.reg .pred p;\n"
      "W_%=:\n"
      "mbarrier.try_wait.parity.shared::cta.b64 p, [%0], %1;\n"
      "@!p bra W_%=;\n}\n"
      ::"r"(bar), "r"(parity) : "memory");
}
__device__ __forceinline__ uint32_t mbar_poll(uint32_t bar) {
  uint32_t done;
  asm volatile(
      "{\n.reg .pred p;\n"
      "mbarrier.test_wait.parity.shared::cta.b64 p, [%1], 0;\n"
      "selp.u32 %0, 1, 0, p;\n}\n"
      : "=r"(done)
      : "r"(bar)
      : "memory");
  return done;
}
__device__ __forceinline__ uint32_t clock32() {
  uint32_t c;
  asm volatile("mov.u32 %0, %%clock;\n" : "=r"(c)::"memory");
  return c;
}
__device__ __forceinline__ int lane_now() {
  int l;
  asm volatile("mov.u32 %0, %%laneid;\n" : "=r"(l));
  return l;
}
__device__ __forceinline__ void wait_until(uint32_t t0, uint32_t dt) {
  while (clock32() - t0 < dt) __nanosleep(40);
}
__device__ __forceinline__ void tma_load_x(uint32_t dst, const CUtensorMap* tm, uint32_t bar, uint32_t bytes, int c0, int c1, int c2) {
  if (bytes) mbar_expect_tx(bar, bytes);
  asm volatile(
      "cp.async.bulk.tensor.3d.shared::cluster.global.mbarrier::complete_tx::bytes [%0], [%1, {%3, %4, %5}], [%2];\n" ::"r"(dst),
      "l"(reinterpret_cast<uint64_t>(tm)), "r"(bar), "r"(c0), "r"(c1), "r"(c2)
      : "memory");
}
__device__ __forceinline__ void tma_load_x4(uint32_t dst, const CUtensorMap* tm, uint32_t bar, int c, int y, int pair) {
  asm volatile(
      "cp.async.bulk.tensor.4d.shared::cluster.global.mbarrier::complete_tx::bytes [%0], [%1, {%3, %6, %4, %5}], [%2];\n" ::"r"(dst),
      "l"(reinterpret_cast<uint64_t>(tm)), "r"(bar), "r"(c), "r"(y), "r"(pair), "r"(0)
      : "memory");
}
__device__ __forceinline__ void tma_load_o(uint32_t dst, const CUtensorMap* tm, uint32_t bar, int x, int y) {
  asm volatile(
      "cp.async.bulk.tensor.2d.shared::cluster.global.mbarrier::complete_tx::bytes [%0], [%1, {%3, %4}], [%2];\n" ::"r"(dst),
      "l"(reinterpret_cast<uint64_t>(tm)), "r"(bar), "r"(x * 9), "r"(y)
      : "memory");
}
__device__ __forceinline__ void tma_load_w(uint32_t dst, const CUtensorMap* tm, uint32_t bar, int c, int kj, int ki, uint32_t mask) {
  asm volatile(
      "cp.async.bulk.tensor.5d.shared::cluster.global.mbarrier::complete_tx::bytes.multicast::cluster [%0], [%1, {%3, %4, "
      "%3, %5, %6}], [%2], %7;\n" ::"r"(dst),
      "l"(reinterpret_cast<uint64_t>(tm)), "r"(bar), "r"(0), "r"(c), "r"(kj), "r"(ki), "h"((uint16_t)mask)
      : "memory");
}
__device__ __forceinline__ void bulk_load_mc(uint32_t dst, const void* src, uint32_t bytes, uint32_t bar) {
  asm volatile(
      "cp.async.bulk.shared::cluster.global.mbarrier::complete_tx::bytes.multicast::cluster [%0], [%1], %2, [%3], %4;\n" ::"r"(dst),
      "l"(src), "r"(bytes), "r"(bar), "h"((uint16_t)3)
      : "memory");
}
__device__ __forceinline__ void tma_store(const CUtensorMap* tm, uint32_t src, int c1, int c2, int c3) {
  asm volatile("cp.async.bulk.tensor.5d.global.shared::cta.bulk_group [%0, {%2, %3, %4, %5, %2}], [%1];\n" ::"l"(
                   reinterpret_cast<uint64_t>(tm)),
               "r"(src), "r"(0), "r"(c1), "r"(c2), "r"(c3)
               : "memory");
  asm volatile("cp.async.bulk.commit_group;\n" ::: "memory");
}
__device__ __forceinline__ constexpr uint64_t w_desc(uint32_t saddr) {
  return (uint64_t)((saddr & 0x3FFFF) >> 4) | ((uint64_t)(1024 >> 4) << 16) | ((uint64_t)(512 >> 4) << 32) | ((uint64_t)2 << 62);
}
__device__ __forceinline__ constexpr uint64_t a_desc(uint32_t saddr) {
  return (uint64_t)((saddr & 0x3FFFF) >> 4) | ((uint64_t)1 << 16) | ((uint64_t)(VROW >> 4) << 32) | ((uint64_t)2 << 62);
}
#define ACC_OPERANDS(c, d)                                                                                        \
  c(d[0]), c(d[1]), c(d[2]), c(d[3]), c(d[4]), c(d[5]), c(d[6]), c(d[7]), c(d[8]),      \
      c(d[9]), c(d[10]), c(d[11]), c(d[12]), c(d[13]), c(d[14]), c(d[15]), c(d[16]),       \
      c(d[17]), c(d[18]), c(d[19]), c(d[20]), c(d[21]), c(d[22]), c(d[23]), c(d[24]),      \
      c(d[25]), c(d[26]), c(d[27]), c(d[28]), c(d[29]), c(d[30]), c(d[31]), c(d[32]),      \
      c(d[33]), c(d[34]), c(d[35]), c(d[36]), c(d[37]), c(d[38]), c(d[39]), c(d[40]),      \
      c(d[41]), c(d[42]), c(d[43]), c(d[44]), c(d[45]), c(d[46]), c(d[47])
#define ACC_LIST                                                                   \
  "{%0, %1, %2, %3, %4, %5, %6, %7, %8, %9, %10, %11, %12, %13, %14, %15, "        \
  "%16, %17, %18, %19, %20, %21, %22, %23, %24, %25, %26, %27, %28, %29, %30, %31, " \
  "%32, %33, %34, %35, %36, %37, %38, %39, %40, %41, %42, %43, %44, %45, %46, %47}, "
__device__ __forceinline__ void wgmma_ss(float* d, uint64_t adesc, uint64_t bdesc, uint32_t accumulate) {
  asm volatile(
      "{\n.reg .pred p;\nsetp.ne.b32 p, %50, 0;\n"
      "wgmma.mma_async.sync.aligned.m64n96k16.f32.bf16.bf16 " ACC_LIST "%48, %49, p, 1, 1, 0, 1;\n}\n"
      : ACC_OPERANDS("+f", d)
      : "l"(adesc), "l"(bdesc), "r"(accumulate));
}
__device__ __forceinline__ void wgmma_def(float* d, uint64_t desc, uint32_t on) {
  asm volatile(
      "{\n.reg .pred p, q;\nsetp.ne.b32 p, 0, 0;\nsetp.ne.b32 q, %49, 0;\n"
      "@q wgmma.mma_async.sync.aligned.m64n96k16.f32.bf16.bf16 " ACC_LIST "%48, %48, p, 1, 1, 1, 1;\n}\n"
      : ACC_OPERANDS("=f", d)
      : "l"(desc), "r"(on));
}
__device__ __forceinline__ void wgmma_rs(float* d, const uint32_t* a, uint64_t bdesc, uint32_t accumulate = 1) {
  asm volatile(
      "{\n.reg .pred p;\nsetp.ne.b32 p, %53, 0;\n"
      "wgmma.mma_async.sync.aligned.m64n96k16.f32.bf16.bf16 " ACC_LIST "{%48, %49, %50, %51}, %52, p, 1, 1, 1;\n}\n"
      : ACC_OPERANDS("+f", d)
      : "r"(a[0]), "r"(a[1]), "r"(a[2]), "r"(a[3]), "l"(bdesc), "r"(accumulate));
}
__device__ __forceinline__ void wgmma_fence() { asm volatile("wgmma.fence.sync.aligned;\n" ::: "memory"); }
__device__ __forceinline__ void wgmma_commit() { asm volatile("wgmma.commit_group.sync.aligned;\n" ::: "memory"); }
template <int N>
__device__ __forceinline__ void wgmma_wait() { asm volatile("wgmma.wait_group.sync.aligned %0;\n" ::"n"(N) : "memory"); }
__device__ __forceinline__ void acc_fence(float* d) {
#pragma unroll
  for (int i = 0; i < 48; i++) asm volatile("" : "+f"(d[i])::"memory");
}
#define UPD(text, d, e, c) asm volatile("{\n.reg .pred p;\nsetp.eq.u32 p, %3, 0;\n@p " text ";\n}\n" : "+f"(d) : "f"(e), "f"(c), "r"(guard))
#define UPD_ADD(d, e, c) UPD("fma.rn.f32 %0, %1, %2, %0", d, e, c)
#define UPD_MUL(d, e, c) UPD("fma.rn.f32 %0, %0, %2, %1", d, e, c)
__device__ __forceinline__ void keep_alive8(const uint32_t* a, uint32_t never) {
  asm volatile(
      "{\n.reg .pred p, q;\nsetp.eq.u32 p, %8, 16;\nsetp.eq.u32 q, %8, 32;\n"
      "@p st.shared.v4.b32 [%8], {%0, %1, %2, %3};\n@q st.shared.v4.b32 [%8], {%4, %5, %6, %7};\n}\n" ::"r"(a[0]),
      "r"(a[1]), "r"(a[2]), "r"(a[3]), "r"(a[4]), "r"(a[5]), "r"(a[6]), "r"(a[7]), "r"(never)
      : "memory");
}
__device__ __forceinline__ void keep_alive4(const uint32_t* a, uint32_t never) {
  asm volatile("{\n.reg .pred p;\nsetp.eq.u32 p, %4, 16;\n@p st.shared.v4.b32 [%4], {%0, %1, %2, %3};\n}\n" ::"r"(a[0]), "r"(a[1]), "r"(a[2]),
               "r"(a[3]), "r"(never) : "memory");
}
__device__ __forceinline__ void ldsm4(uint32_t& r0, uint32_t& r1, uint32_t& r2, uint32_t& r3, uint32_t addr) {
  asm volatile("ldmatrix.sync.aligned.m8n8.x4.shared.b16 {%0, %1, %2, %3}, [%4];\n"
               : "=r"(r0), "=r"(r1), "=r"(r2), "=r"(r3)
               : "r"(addr)
               : "memory");
}
__device__ __forceinline__ void ldsm4(uint32_t* r, uint32_t addr) { ldsm4(r[0], r[1], r[2], r[3], addr); }
__device__ __forceinline__ void stsm4(uint32_t addr, const uint32_t* r) {
  asm volatile("stmatrix.sync.aligned.m8n8.x4.shared.b16 [%0], {%1, %2, %3, %4};\n" ::"r"(addr), "r"(r[0]), "r"(r[1]), "r"(r[2]), "r"(r[3])
               : "memory");
}
__device__ __forceinline__ void arrive_if(uint32_t bar) {
  asm volatile("{\n.reg .pred p;\nsetp.ne.u32 p, %0, 0;\n@p mbarrier.arrive.shared::cluster.b64 _, [%0];\n}\n" ::"r"(bar) : "memory");
}
__device__ __forceinline__ uint32_t lds32(uint32_t addr) {
  uint32_t v;
  asm volatile("ld.shared.u32 %0, [%1];\n" : "=r"(v) : "r"(addr) : "memory");
  return v;
}
__device__ __forceinline__ void lds64(uint32_t& a, uint32_t& b, uint32_t addr) {
  asm volatile("ld.shared.v2.u32 {%0, %1}, [%2];\n" : "=r"(a), "=r"(b) : "r"(addr) : "memory");
}
__device__ __forceinline__ void lds128(uint32_t* v, uint32_t addr) {
  asm volatile("ld.shared.v4.b32 {%0, %1, %2, %3}, [%4];\n" : "=r"(v[0]), "=r"(v[1]), "=r"(v[2]), "=r"(v[3]) : "r"(addr) : "memory");
}
__device__ __forceinline__ void sts128(uint32_t addr, const uint32_t* v) {
  asm volatile("st.shared.v4.b32 [%0], {%1, %2, %3, %4};\n" ::"r"(addr), "r"(v[0]), "r"(v[1]), "r"(v[2]), "r"(v[3]) : "memory");
}
__device__ __forceinline__ void sts64(uint32_t addr, const uint32_t* v) {
  asm volatile("st.shared.v2.b32 [%0], {%1, %2};\n" ::"r"(addr), "r"(v[0]), "r"(v[1]) : "memory");
}
__device__ __forceinline__ void sts32(uint32_t addr, uint32_t v) {
  asm volatile("st.shared.u32 [%0], %1;\n" ::"r"(addr), "r"(v) : "memory");
}
__device__ __forceinline__ void fence_async() { asm volatile("fence.proxy.async.shared::cta;\n" ::: "memory"); }
__device__ __forceinline__ void bar_sync(int id, int n) { asm volatile("bar.sync %0, %1;\n" ::"r"(id), "r"(n) : "memory"); }
__device__ __forceinline__ __nv_bfloat162 as_bf2(uint32_t v) { return *reinterpret_cast<__nv_bfloat162*>(&v); }
__device__ __forceinline__ uint32_t as_u32(__nv_bfloat162 v) { return *reinterpret_cast<uint32_t*>(&v); }
__device__ __forceinline__ uint32_t hfma2(uint32_t c, uint32_t a, uint32_t b) { return as_u32(__hfma2(as_bf2(c), as_bf2(a), as_bf2(b))); }
__device__ __forceinline__ uint32_t hadd2(uint32_t a, uint32_t b) { return as_u32(__hadd2(as_bf2(a), as_bf2(b))); }
__device__ __forceinline__ uint32_t hsub2(uint32_t a, uint32_t b) { return as_u32(__hsub2(as_bf2(a), as_bf2(b))); }
__device__ __forceinline__ __nv_bfloat162 half_of(uint32_t w, int hi) { return hi ? __high2bfloat162(as_bf2(w)) : __low2bfloat162(as_bf2(w)); }
__device__ __forceinline__ uint32_t hmul2_h(uint32_t w, int hi, uint32_t a) { return as_u32(__hmul2(half_of(w, hi), as_bf2(a))); }
__device__ __forceinline__ uint32_t hfma2_h(uint32_t w, int hi, uint32_t a, uint32_t c) {
  return as_u32(__hfma2(half_of(w, hi), as_bf2(a), as_bf2(c)));
}
__device__ __forceinline__ uint32_t pack2(float lo, float hi) { return as_u32(__floats2bfloat162_rn(lo, hi)); }
__device__ __forceinline__ uint32_t prmt(uint32_t a, uint32_t b, uint32_t sel) {
  uint32_t r;
  asm("prmt.b32 %0, %1, %2, %3;\n" : "=r"(r) : "r"(a), "r"(b), "r"(sel));
  return r;
}
__device__ __forceinline__ uint32_t absmax2(uint32_t a, uint32_t b) {
  uint32_t r;
  asm("max.NaN.xorsign.abs.bf16x2 %0, %1, %2;\n" : "=r"(r) : "r"(a), "r"(b));
  return r;
}
__device__ __forceinline__ uint32_t clip2(uint32_t p) {
  return as_u32(__hmin2(__hmax2(as_bf2(p), as_bf2(0u)), as_bf2(0x435f435fu)));
}
__device__ __forceinline__ constexpr uint32_t tap_delta(int a, int b) {
  return (a == 0 ? 0xbf80u : a == 1 ? 0u : 0x3f80u) | (b == 0 ? 0xbf800000u : b == 1 ? 0u : 0x3f800000u);
}
__device__ __forceinline__ void coefs(uint32_t w, uint32_t& p0, uint32_t& p1) {
  const uint32_t o = hsub2(0x3f803f80u, w);
  const uint32_t xa = __byte_perm(o, w, 0x7632);
  p0 = hmul2_h(o, 0, xa);
  p1 = hmul2_h(w, 0, xa);
}
__device__ __forceinline__ uint32_t frac2(uint32_t pos) {
  const float py = bf16lo(pos), px = bf16hi(pos);
  return __byte_perm(__float_as_uint(py - floorf(py)), __float_as_uint(px - floorf(px)), 0x7632);
}
__device__ __forceinline__ void blend4(uint32_t* t, const uint32_t* g, const uint32_t* h, const uint32_t* k, uint32_t a0,
                                       uint32_t a1, uint32_t b0, uint32_t b1) {
#pragma unroll
  for (int i = 0; i < 4; i++) {
    const uint32_t p0 = (i & 1) ? b0 : a0, p1 = (i & 1) ? b1 : a1;
    t[i] = hfma2_h(p1, 1, k[i], hfma2_h(p1, 0, h[i], hfma2_h(p0, 1, g[i], hmul2_h(p0, 0, t[i]))));
  }
}
__device__ __forceinline__ bool elect_one() {
  uint32_t r;
  asm volatile("{\n.reg .pred p;\nelect.sync _|p, 0xffffffff;\nselp.u32 %0, 1, 0, p;\n}\n" : "=r"(r));
  return r != 0;
}

template <int N>
__device__ __forceinline__ void transform6(const uint32_t (*a)[N], const uint32_t (*b)[N], const uint32_t (*c)[N], uint32_t dst, uint32_t off0) {
  const uint32_t* d[6] = {a[0], a[1], b[0], b[1], c[0], c[1]};
  uint32_t v[N], t[N], u[N];
  auto put = [&](int slot, const uint32_t* r) {
    const uint32_t p = slot < 4 ? dst + slot * VSLOT : dst + off0 + (slot - 4) * VSLOT;
    if (N == 4) sts128(p, r);
    else sts64(p, r);
  };
#pragma unroll
  for (int k = 0; k < 2; k++) {
#pragma unroll
    for (int i = 0; i < N; i++) v[i] = hfma2(0xc088c088u, d[2 + k][i], hadd2(d[k][i], d[4 + k][i]));
    put(4 + k, v);
  }
#pragma unroll
  for (int k = 0; k < 2; k++) {
    const uint32_t q = k ? 0xbe80be80u : 0xc080c080u, f = k ? 0x40004000u : 0x3f003f00u;
#pragma unroll
    for (int i = 0; i < N; i++) {
      t[i] = hfma2(q, d[2][i], d[4][i]);
      u[i] = hfma2(q, d[1][i], d[3][i]);
      v[i] = hfma2(f, u[i], t[i]);
    }
    put(2 * k, v);
#pragma unroll
    for (int i = 0; i < N; i++) t[i] = hfma2(f ^ 0x80008000u, u[i], t[i]);
    put(2 * k + 1, t);
  }
}

template <bool FP32>
__device__ __forceinline__ void weights4(const uint32_t* g0, const uint32_t* g1, const uint32_t* g2, uint32_t (*u)[4]) {
#pragma unroll
  for (int i = 0; i < 4; i++) {
    if (FP32) {
      float r[4][2];
#pragma unroll
      for (int h = 0; h < 2; h++) {
        const float a = h ? bf16hi(g0[i]) : bf16lo(g0[i]), b = h ? bf16hi(g1[i]) : bf16lo(g1[i]), c = h ? bf16hi(g2[i]) : bf16lo(g2[i]);
        const float ea = fmaf(0.25f, c, a) * -0.5f, eb = fmaf(0.25f, a, c);
        r[0][h] = fmaf(-0.25f, b, ea);
        r[1][h] = fmaf(0.25f, b, ea);
        r[2][h] = fmaf(0.5f, b, eb);
        r[3][h] = fmaf(-0.5f, b, eb);
      }
#pragma unroll
      for (int k = 0; k < 4; k++) u[k][i] = pack2(r[k][0], r[k][1]);
    } else {
      const uint32_t ea = hfma2(0xbe00be00u, g2[i], as_u32(__hmul2(as_bf2(g0[i]), as_bf2(0xbf00bf00u))));
      u[0][i] = hfma2(0xbe80be80u, g1[i], ea);
      u[1][i] = hfma2(0x3e803e80u, g1[i], ea);
      const uint32_t eb = hfma2(0x3e803e80u, g0[i], g2[i]);
      u[2][i] = hfma2(0x3f003f00u, g1[i], eb);
      u[3][i] = hfma2(0xbf00bf00u, g1[i], eb);
    }
  }
}

template <int GROUP = 4096>
__device__ __forceinline__ void stage_slab(const float* acc, uint32_t stg, int lane) {
  const uint32_t a = stg + (lane & 15) * 64 + (((lane >> 4) ^ ((lane >> 1) & 3)) << 4);
#pragma unroll
  for (int jp = 0; jp < 6; jp++) {
    uint32_t pk[4];
#pragma unroll
    for (int i = 0; i < 4; i++) pk[i] = pack2(acc[jp * 8 + i * 2], acc[jp * 8 + i * 2 + 1]);
    stsm4((a ^ ((jp & 1) * 32)) + (jp >> 1) * GROUP, pk);
  }
}
__device__ __forceinline__ void publish(uint32_t bar, int lane) {
  fence_async();
  __syncwarp();
  arrive_if(lane == 0 ? bar : 0u);
}
__device__ __forceinline__ constexpr uint32_t w_slot(int st) {
  return st < 3 ? SM_WW + st * STAGE : st == 3 ? 12 * VSLOT : st < 11 ? SM_WW + (st - 4) % 3 * STAGE : st < 13 ? 4 * VSLOT + (st - 11) * STAGE
         : st < 16 ? SM_WW + st % 3 * STAGE : st == 16 ? 4 * VSLOT : STAGE;
}
__device__ __forceinline__ constexpr uint64_t w_slots(int st0, int step, int n) {
  uint64_t r = 0;
  for (int i = 0; i < n; i++) r |= (uint64_t)(w_slot(st0 + i * step) >> 10) << (8 * i);
  return r;
}
__device__ __forceinline__ uint32_t w_stg(int wg, int i) {
  return wg ? (i == 2 ? 0 : i == 1 ? SM_R + 24576 : i == 0 ? 4 * VSLOT + STAGE : SM_WW + STAGE) : SM_R + (i == 2 ? 24576 : (i & 1) * 12288);
}

__device__ __forceinline__ void ldsm4_if(uint32_t* r, uint32_t addr, uint32_t on) {
  asm volatile(
      "{\n.reg .pred p;\nsetp.ne.u32 p, %5, 0;\n"
      "@p ldmatrix.sync.aligned.m8n8.x4.shared.b16 {%0, %1, %2, %3}, [%4];\n}\n"
      : "+r"(r[0]), "+r"(r[1]), "+r"(r[2]), "+r"(r[3])
      : "r"(addr), "r"(on)
      : "memory");
}
__device__ __forceinline__ void push_record(uint32_t bars, uint32_t key, uint32_t pos) {
  uint32_t slot;
  asm volatile("atom.shared.add.u32 %0, [%1], 1;\n" : "=r"(slot) : "r"(bars + O_CNT) : "memory");
  const uint32_t v[2] = {key, pos};
  if (slot < NREC) sts64(bars + O_REC + slot * 8, v);
}
__device__ __forceinline__ void put_sel(uint32_t bars, uint32_t key, int lane) {
  if (lane < NREC)
    asm volatile("st.shared.u16 [%0], %1;\n" ::"r"(bars + O_SEL + (lane & 6) * 4 + (lane >> 3) * 4 + (lane & 1) * 2), "h"((uint16_t)((key >> 20) | 0x4000u)) : "memory");
}
__device__ __noinline__ void push_taps(uint32_t bars, uint32_t key, uint32_t taps, const uint32_t* __restrict__ offs) {
  const int y = key & 255, x = (key >> 8) & 255;
#pragma unroll 1
  for (; taps; taps &= taps - 1) {
    const int tap = __ffs(taps) - 1, ki = (tap * 11) >> 5;
    const uint32_t gp = pack2((float)(y + ki - 1), (float)(x + tap - ki * 3 - 1));
    push_record(bars, key | (tap << 16), clip2(hadd2(gp, __ldg(offs + (y * IW + x) * 9 + tap))));
  }
}
__device__ __forceinline__ uint32_t wino_key(int y, int x) {
  return y | (x << 8) | ((((y & 28) << 1) | (x & 7)) << 20) | ((((x & 8) >> 1) | (y & 3)) << 27);
}
__device__ __forceinline__ uint32_t strip_key(int u, int v, int left) {
  return (left ? v | (u << 8) : u | (v << 8)) | ((((u & 15) << 3) | (v & 7)) << 20) | ((u >> 4) << 29);
}
__device__ __forceinline__ bool strip_off(uint32_t d, bool out) { return (d & 0x7fff) || (d & 0x7fff7fffu) > (out ? 0u : 0x3f000000u); }
__device__ __forceinline__ void delta(uint32_t* v, uint32_t key, uint32_t pos, const uint4* __restrict__ x, int c) {
  const int tap = (key >> 16) & 15, ki = (tap * 11) >> 5, gy = (int)bf16lo(pos), gx = (int)bf16hi(pos);
  const int cy = min(max((int)(key & 255) + ki - 1, 0), IH - 1), cx = min(max((int)((key >> 8) & 255) + tap - ki * 3 - 1, 0), IW - 1);
  const uint32_t sx = gx < IW - 1 ? 12 : 0, sy = gy < IH - 1 ? IW * 12 : 0, p = (gy * IW + gx) * 12 + c;
  uint4 t[5] = {__ldg(x + p), __ldg(x + (p + sx)), __ldg(x + (p + sy)), __ldg(x + (p + sy + sx)), __ldg(x + (uint32_t)((cy * IW + cx) * 12 + c))};
  uint32_t q0, q1;
  coefs(frac2(pos), q0, q1);
  blend4(&t[0].x, &t[1].x, &t[2].x, &t[3].x, q0, q1, q0, q1);
#pragma unroll
  for (int i = 0; i < 4; i++) v[i] = hsub2((&t[0].x)[i], (&t[4].x)[i]);
}
__device__ __forceinline__ void fixup(uint32_t bars, int w, int n, const uint4* __restrict__ x, const uint4* __restrict__ wgt) {
  const uint32_t fix = bars + SM_FIX - SM_BAR + 3072, part = fix + 3072;
  const int lane = lane_now(), l = min(lane, 23), up = l >= 12;
#pragma unroll 1
  for (int r = 0; r < n; r++) {
    uint32_t key, pos, sum[4];
    lds64(key, pos, bars + O_REC + r * 8);
    key = __shfl_sync(0xffffffffu, key, 0);
    pos = __shfl_sync(0xffffffffu, pos, 0);
    delta(sum, key, pos, x, w * 3 + (l >> 3));
    sts128(part + w * 192 + (l >> 3) * 16, sum);
    __syncwarp();
#pragma unroll
    for (int i = 0; i < 4; i++) sum[i] = 0;
    const uint4* wp = wgt + (((key >> 16) & 15) * 96 + w * 24 + up * 11) * 12 + l;
#pragma unroll 1
    for (int h = 0; h < 3; h++) {
      uint4 wv[4];
      uint32_t d[2];
#pragma unroll
      for (int k = 0; k < 4; k++) wv[k] = __ldg(wp + (h * 4 + k) * 12);
      lds64(d[0], d[1], part + w * 192 + up * 24 + h * 8);
#pragma unroll
      for (int i = 0; i < 4; i++)
        sum[i] = hadd2(sum[i], hfma2_h(d[1], 1, (&wv[3].x)[i], hfma2_h(d[1], 0, (&wv[2].x)[i], hfma2_h(d[0], 1, (&wv[1].x)[i], hmul2_h(d[0], 0, (&wv[0].x)[i])))));
    }
#pragma unroll
    for (int i = 0; i < 4; i++) sum[i] = hadd2(sum[i], __shfl_down_sync(0xffffffffu, sum[i], 12));
    if (lane < 12) sts128(part + w * 192 + lane * 16, sum);
    bar_sync(4, 128);
    if (lane < 12) {
      float lo = 0.0f, hi = 0.0f;
#pragma unroll
      for (int k = 0; k < 4; k++) {
        const uint32_t v = lds32(part + k * 192 + w * 48 + lane * 4);
        lo += bf16lo(v);
        hi += bf16hi(v);
      }
      sts32(fix + r * 192 + w * 48 + lane * 4, pack2(lo, hi));
    }
    bar_sync(4, 128);
  }
}
__device__ __forceinline__ void select_rows(uint32_t* A, const uint32_t* sel, uint32_t code, bool scale) {
#pragma unroll
  for (int i = 0; i < 4; i++) {
    A[i] = as_u32(__heq2(as_bf2(sel[i >> 1]), as_bf2(code + (i & 1) * 0x80008u)));
    if (scale) A[i] = as_u32(__hmul2(as_bf2(A[i]), as_bf2(0x3ff03ff0u)));
  }
}
struct Maps {
  CUtensorMap x[5];
  CUtensorMap w[2];
  CUtensorMap o[2];
  CUtensorMap out[4];
};

__global__ void __cluster_dims__(2, 1, 1) __launch_bounds__(NTHREADS, 1)
dcn_kernel(const __nv_bfloat16* __restrict__ x, const uint32_t* __restrict__ offs, const uint4* __restrict__ wgt, Scratch* scr,
           const uint32_t never, const __grid_constant__ Maps tm) {
  extern __shared__ __align__(1024) uint8_t smem[];
  const uint32_t sbase = smem_u32(smem);
  const uint32_t bars = sbase + SM_BAR;
  const uint32_t tstart = clock32();
  const int tid = threadIdx.x;
  const int cta = blockIdx.x - NC;
  const int wid = __shfl_sync(0xffffffffu, tid >> 5, 0);
  const int lane = tid & 31;
  const bool wino = (uint32_t)cta < NW, strip = cta >= NW;
  const int left = (uint32_t)cta >= NW + NG / 2;
  const int ry = (cta * 43) >> 9;
  const int x0 = wino ? 32 + (cta - ry * 12) * 16 : 32 + (cta - NW - left * (NG / 2)) * 8, y0 = 32 + ry * 32;
  auto load_cols = [&](int s, int j) {
    const uint32_t dst = sbase + (s ? SM_R : 4 * VSLOT) + j * 2 * PIECE, bar = bars + (B_XF + s * 5 + j) * 8;
    if (j < 4) tma_load_x4(dst, &tm.x[4], bar, s * 32, y0 - 1, (x0 >> 1) - 1 + j * 2);
    else tma_load_x(dst, &tm.x[0], bar, 0, s * 32, x0 + 15, y0 - 1);
  };
  auto corner_tile = [&](int wg) {
    const uint32_t t = ((wg ? 0xfeba00000000ull : 0xd976c8325410ull) >> (4 * (cta + NC))) & 15;
    return (t & 3) | ((t >> 2) << 8);
  };
  auto load_cx = [&](int wg, int g, uint32_t tl) {
    tma_load_x(sbase + SM_CX + wg * CWIN + g * CSLICE, &tm.x[3], bars + (B_XF + wg * 3 + g) * 8, CSLICE, g * 32, (int)(tl & 255) * 8 - 2,
               (int)(tl >> 8) * 8 - 2);
  };
  const bool one = elect_one();
  if (wid == 0 && one) {
    asm volatile("prefetch.tensormap [%0];\n" ::"l"(reinterpret_cast<uint64_t>(wino ? &tm.x[4] : &tm.o[1])) : "memory");
    asm volatile("prefetch.tensormap [%0];\n" ::"l"(reinterpret_cast<uint64_t>(&tm.x[0])) : "memory");
  }
  if (wid == 15) {
    if (one) {
      if (wino) {
        mbar_init(bars + B_W2 * 8, 1);
#pragma unroll
        for (int k = 0; k < 9; k++)
          asm volatile("cp.async.bulk.shared::cluster.global.mbarrier::complete_tx::bytes [%0], [%1], 6144, [%2];\n" ::"r"(sbase + k * 6144 + (k < 6 ? 0 : 6 * VSLOT)),
                       "l"(wgt + k * 1152), "r"(bars + B_W2 * 8) : "memory");
      }
#pragma unroll
      for (int j = 0; j < 8; j++) mbar_init(bars + j * 8, 1);
      if (wino) {
#pragma unroll
        for (int j = 0; j < 5; j++) load_cols(0, j);
        mbar_expect_tx(bars + B_W2 * 8, 9 * 6144);
      } else {
        mbar_expect_tx(bars + B_OG * 8, strip ? 4 * 2304 : 2 * 2304);
#pragma unroll
        for (int k = 0; k < 4; k++) {
          const uint32_t tl = corner_tile(k & 1);
          if (strip || k < 2)
            tma_load_o(sbase + (strip ? SM_GO + k * 2304 : SM_CX + k * CWIN + 2 * CSLICE), &tm.o[1], bars + B_OG * 8,
                       strip ? (left ? k * 8 : x0) : (tl & 255) * 8, strip ? (left ? x0 : k * 8) : (tl >> 8) * 8);
        }
        if (strip) {
          asm volatile("prefetch.tensormap [%0];\n" ::"l"(reinterpret_cast<uint64_t>(&tm.x[1 + left])) : "memory");
        } else {
          load_cx(0, 0, corner_tile(0));
          if (cta >= -4) load_cx(1, 0, corner_tile(1));
        }
        asm volatile("prefetch.tensormap [%0];\n" ::"l"(reinterpret_cast<uint64_t>(&tm.w[left])) : "memory");
      }
      asm volatile("fence.mbarrier_init.release.cluster;\n" ::: "memory");
    }
    __syncwarp();
  }
  const bool prep = wid >= 8 && wid < 11 && strip && cta < NW + 24;
  uint4 g[3];
  if (prep) {
    const uint4* src = wgt + (uint32_t)((cta - NW + ((cta - NW) >> 3) * 4) * 96 + 352 + (tid >> 5) * 4 + (lane >> 2) * 12 + (lane & 3));
#pragma unroll
    for (int k = 0; k < 3; k++) g[k] = __ldg(src + k * 3456);
  }
  if (wid < 8 || wid >= 12) {
    if (one && wid < 15) {
      const int grp = wid < 8 ? 4 + wid : 15 - wid;
#pragma unroll
      for (int i = 0; i < 8; i++) mbar_init(bars + grp * 64 + i * 8, grp < 5 ? 1 : grp < 7 ? 16 : grp < 8 ? 8 : 4);
      asm volatile("fence.mbarrier_init.release.cluster;\n" ::: "memory");
    }
    __syncwarp();
  } else if (one && wid == 11) {
    const uint32_t z[2] = {0, 1u << 31};
    sts64(bars + O_CNT, z);
    __threadfence_block();
  }
  asm volatile("barrier.cluster.arrive.relaxed.aligned;\n" ::: "memory");
  auto load_cw = [&](int st) {
    const uint32_t rank = cta & 1;
    const int g = (st * 11) >> 5;
    const uint32_t fb = bars + (B_WF + st) * 8;
    mbar_expect_tx(fb, STAGE);
    tma_load_w(sbase + st * STAGE, &tm.w[1], fb, g * 32, 0, st - g * 3, 1u << rank);
    tma_load_w(sbase + st * STAGE + STAGE / 2, &tm.w[1], fb, g * 32 + 16, 0, st - g * 3, 1u << rank);
  };
  if (wid < 8) {
    const int wg = wid >> 2, warp = wid & 3, lane = lane_now();
    if ((sbase & 0xffffff) != SB) __trap();
    const int src = cta + NC, t = tid & 127;
    const int lf = src == 0 || src == 7 ? t < 64 : src >= 4;
    const int along = ((0x0c84b842u >> (4 * src)) & 15) * 16 + (src == 0 || src == 7 ? (t >> 1) & 31 : t >> 1);
    const int oy = lf ? along : 32 + (t & 1), ox = lf ? 32 + (t & 1) : along;
    const bool own = src == 0 ? !lf || along >= 34 : along < (src == 2 ? 176 : 224);
    uint32_t o2[9], tag;
    if (src < 8 && wg) {
      tag = scr->launch[blockIdx.x] + 1;
#pragma unroll
      for (int m = 0; m < 9; m++) o2[m] = __ldg(offs + (min(oy, IH - 1) * IW + min(ox, IW - 1)) * 9 + m);
    }
    asm volatile("setmaxnreg.inc.sync.aligned.u32 224;\n");
    asm volatile("barrier.cluster.wait.acquire.aligned;\n" ::: "memory");
    uint32_t we_addr;
    asm volatile("mapa.shared::cluster.u32 %0, %1, %2;\n" : "=r"(we_addr) : "r"(bars + B_WE * 8), "r"(lane & 1));
    const uint32_t nv = never & (uint32_t)tid;
    float acc[4][48];
    int ntiles = 0;
    uint32_t tile0 = 0, tstep = 0;
    if (wino) {
      {
        const uint32_t dst = sbase + (wid & 2) * (STAGE / 4) + (wid & 1) * 512 + (lane >> 2) * 64 + (((lane ^ (lane >> 3)) & 3) << 4);
        const uint32_t src = sbase + warp * 1536 + (lane >> 2) * 192 + (lane & 3) * 16;
        mbar_wait(bars + B_W2 * 8);
        uint32_t gg[3][4], u[4][4];
        auto get = [&](int n) {
          const uint32_t a = src + n * 64 + ((n * 11) >> 5) * (6144 - 192);
          lds128(gg[0], a);
          lds128(gg[2], a + 10 * VSLOT);
          lds128(gg[1], a + 18432);
        };
        get(wg);
#pragma unroll 1
        for (int n = wg; n < 9; n += 2) {
          weights4<false>(gg[0], gg[1], gg[2], u);
          if (n < 7) get(n + 2);
#pragma unroll
          for (int k = 0; k < 4; k++) sts128(dst + n * 1024 + w_slot(k), u[k]);
        }
        fence_async();
        bar_sync(12, 384);
      }
      {
        const int q = wid + wg, tp = lane >> 3, h = tp * 18 + q;
        const uint32_t src = (sbase + 4 * VSLOT + q * PIECE + tp * 1024 + (lane & 7) * 16) & (x0 + 2 * q == IW ? ~64u : ~0u);
        const uint32_t vb = sbase + h * 128 + (lane & 4) * 16;
        mbar_wait(bars + (B_XF + (q >> 1)) * 8);
        uint32_t d[10][4];
#pragma unroll
        for (int r = 0; r < 9; r++) lds128(d[r], src + r * 128);
        lds128(d[9], src + (y0 + 32 == IH && tp == 3 ? 8 * 128 : 9 * 128));
        transform6<4>(d, d + 2, d + 4, vb + (((lane ^ h) & 3) << 4), 10 * VSLOT);
        transform6<4>(d + 4, d + 6, d + 8, vb + VROW + (((lane ^ (h + 1)) & 3) << 4), 10 * VSLOT);
        publish(bars + (wg ? B_VF + 1 : B_V0) * 8, lane);
      }
      constexpr uint64_t bd0 = w_desc(SB);
      const uint64_t ad0 = a_desc(SB) + wg * 32;
      uint32_t rel = 0;
      if (lane == 3) we_addr = bars + (B_VE - 3) * 8;
      if (lane == 2) we_addr = bars + (B_WL - 13) * 8;
      uint32_t guard = never, gnext = never;
#define PIN_NEXT do { guard = gnext; gnext = clock32() & never; } while (0)
      auto stage = [&](float* a, int st, uint32_t rs, int vslot, uint32_t accumulate, auto work, bool retire = true, bool await = true) {
        const uint64_t bd = bd0 + (rs >> 4), ad = ad0 + vslot * (VSLOT >> 4);
        if (await) mbar_wait(bars + (B_WF + st) * 8);
        wgmma_fence();
#pragma unroll
        for (int j = 0; j < 6; j++) {
          wgmma_ss(a, ad + (j >> 1) * 4 + (j & 1) * 2, bd + (j >> 1) * WTAP + (j & 1) * WHALF, j ? 1 : accumulate);
          if (j == 1 && retire) {
            wgmma_commit();
            wgmma_wait<1>();
            arrive_if(rel);
            rel = ((lane < 2 ? 0xff7u : lane == 3 ? 8u : lane == 2 ? 0x2000u : 0u) >> st) & 1 ? we_addr + st * 8 : 0u;
          }
          if (j == 5) wgmma_commit();
          work(j);
        }
      };
#pragma unroll
      for (int p = 0; p < 4; p++) {
        wgmma_fence();
        wgmma_def(acc[p], w_desc(SB + SM_WW), never);
      }
      wgmma_commit();
      mbar_wait(bars + B_V0 * 8);
      if (wg) mbar_wait(bars + (B_VF + 1) * 8);
#pragma unroll 1
      for (int s = 0; s < 3; s++) {
        if (s) {
          const uint32_t vf = bars + (B_VF + 2 * s + wg) * 8;
          if (!__all_sync(0xffffffffu, mbar_poll(vf)) || (wg && s == 2)) {
            wgmma_wait<0>();
            arrive_if(rel);
            rel = 0;
            if (wg && s == 2) mbar_wait(bars + B_PP * 8);
            mbar_wait(vf);
          }
        }
#pragma unroll
        for (int p = 0; p < 4; p++) {
          stage(acc[p], s * 4 + p, (((uint32_t)w_slots(p, 4, 3) >> (8 * s)) & 255) << 10, (s & 1) * 4 + p, s, [&](int j) {
            if (p == 3 && j == 1) arrive_if(lane == 0 && !wg && s == 2 ? bars + B_PP * 8 : 0u);
          });
        }
      }
      mbar_wait(bars + (B_WF + 12) * 8);
      uint32_t imp = lds32(bars + O_CNT + 4);
#pragma unroll
      for (int i = 0; i < 48; i++) {
        if (i % 8 == 0) PIN_NEXT;
        UPD_ADD(acc[0][i], acc[1][i], 1.0f);
        UPD_MUL(acc[1][i], acc[0][i], -2.0f);
      }
      wgmma_wait<0>();
      arrive_if(rel);
      rel = 0;
      imp = __ballot_sync(0xffffffffu, (imp >> lane) & 1);
      uint32_t sel[2], A[4];
      if ((imp >> (wg * 4)) & ~0xf0f0u) {
        mbar_wait(bars + B_IM * 8);
        if ((int)imp < 0) imp = __ballot_sync(0xffffffffu, (lds32(bars + O_CNT + 4) >> lane) & 1);
        lds64(sel[0], sel[1], bars + O_SEL + (lane & 3) * 8);
      }
      const uint32_t code = (wg * 512 + warp * 16 + (lane >> 2) + 0x4000u) * 0x10001u;
      auto corr = [&](int p) {
#pragma unroll
        for (int i = 0; i < 4; i++) asm volatile("mov.b32 %0, 0;\n" : "=r"(A[i]));
        if ((imp >> (wg * 4 + p)) & 1) {
          select_rows(A, sel, code + p * 0x800080u, p == 1 || p == 2);
          wgmma_fence();
          wgmma_rs(acc[p], A, w_desc(SB + SM_FIX));
          wgmma_commit();
        }
      };
      auto done = [&] {
        wgmma_wait<0>();
        keep_alive4(A, nv);
      };
      auto odd = [&](int i0, int i1) {
#pragma unroll
        for (int i = 0; i < 48; i++) {
          if (i < i0 || i >= i1) continue;
          if (i % 16 == 0) PIN_NEXT;
          UPD_ADD(acc[1][i], acc[3][i], 0.5f);
          UPD_ADD(acc[3][i], acc[1][i], 2.0f / 15.0f);
        }
      };
#pragma unroll
      for (int i = 0; i < 48; i++) {
        if (i % 8 == 0) PIN_NEXT;
        if (i == 24 && !wg) mbar_wait(bars + (B_VF + 5) * 8);
        UPD_ADD(acc[2][i], acc[3][i], 1.0f);
        UPD_MUL(acc[3][i], acc[2][i], -2.0f);
        UPD_ADD(acc[2][i], acc[0][i], 0.5f);
        UPD_ADD(acc[0][i], acc[2][i], 2.0f / 15.0f);
      }
      const uint32_t stg = sbase + warp * 1024, stb = bars + (B_ST + wg * 4) * 8;
      const uint32_t sa = stg + (lane & 15) * 64 + (((lane >> 4) ^ ((lane >> 1) & 3)) << 4);
      uint32_t pk[24];
      auto put = [&](int i, int jp) { stsm4(((sa + guard + w_stg(wg, i)) ^ ((jp & 1) * 32)) + (jp >> 1) * 4096, pk + jp * 4); };
      auto row = [&](int i, int g0, int g1) {
#pragma unroll
        for (int k = g0 * 4; k < g1 * 4; k++) pk[k] = pack2(acc[i][k * 2] * (8.0f / 15.0f), acc[i][k * 2 + 1] * (8.0f / 15.0f));
        PIN_NEXT;
#pragma unroll
        for (int g = g0; g < g1; g++) put(i, g);
      };
      corr(2);
      odd(0, 16);
      done();
      acc_fence(acc[2]);
      row(2, 0, 6);
      corr(0);
      odd(16, 48);
      publish(stb + 16, lane);
      done();
      corr(1);
      auto row1 = [&](int n) {
        if (n == 1) {
          keep_alive4(A, nv);
          acc_fence(acc[1]);
        }
        if (n == 2) mbar_wait(bars + (wg ? B_SR : B_RD) * 8);
        if (n >= 2 && n < 8) row(1, n - 2, n - 1);
        if (n == 9) publish(stb + 8, lane);
      };
      stage(acc[0], 12, w_slot(12), 10, 1, [&](int j) { row1(j); }, true, false);
      stage(acc[0], 13, w_slot(13), 8, 1, [&](int j) { row1(6 + j); });
      stage(acc[0], 14, w_slot(14), 12, 1, [](int) {});
      corr(3);
      guard |= gnext;
      auto row0 = [&](int n) {
        if (n == 2) {
          if (wg) mbar_wait(bars + B_WL * 8);
          acc_fence(acc[0]);
#pragma unroll
          for (int i = 0; i < 24; i++) pk[i] = pack2(acc[0][i * 2], acc[0][i * 2 + 1]);
        }
        if (n >= 2 && n < 5) {
          put(0, n * 2 - 4);
          put(0, n * 2 - 3);
        }
        if (n == 6) publish(stb, lane);
      };
      stage(acc[3], 15, w_slot(15), 11, 1, [&](int j) {
        if (j == 1) keep_alive4(A, nv);
        row0(j);
      });
      stage(acc[3], 16, w_slot(16), 9, 1, [&](int j) { row0(6 + j); }, false);
      stage(acc[3], 17, w_slot(17), 13, 1, [](int) {}, false);
      if (!wg) mbar_wait(bars + (B_SR + 1) * 8);
      wgmma_wait<0>();
      acc_fence(acc[3]);
      stage_slab(acc[3], stg + w_stg(wg, 3), lane);
      publish(stb + 24, lane);
      mbar_wait(bars + B_RD * 8);
      if (lds32(bars + O_CNT) > NREC || imp >= 0x10000u) {
        ntiles = 4;
        tile0 = (x0 >> 3) + wg + (y0 << 5);
        tstep = 0x100;
      }
    } else if (strip) {
      const uint32_t tab = sbase + SM_GT + wid * 1152;
      {
        const int r = (warp & 1) * 4 + (lane & 3), c = lane >> 2, pu = wid * 4 + (lane & 3), pv = x0 + c;
        const uint32_t oa = sbase + SM_GO + (wid >> 1) * 2304 + (left ? c * 8 + r : r * 8 + c) * 36, swap = left ? 0x3210u : 0x1032u;
        uint32_t bad = 0;
        mbar_wait(bars + B_OG * 8);
#pragma unroll 1
        for (int tv = 0; tv < 3; tv++) {
          const uint32_t base = pack2((float)(pv + tv - 1), (float)pu);
#pragma unroll
          for (int tu = 0; tu < 3; tu++) {
            const int tap = left ? tv * 3 + tu : tu * 3 + tv;
            const uint32_t gp = hadd2(base, tap_delta(1, tu));
            uint32_t d = hsub2(clip2(hadd2(gp, prmt(lds32(oa + tap * 4), 0, swap))), clip2(gp));
            const bool out = tu == 0 && pu == 0, off = strip_off(d, out);
            bad |= off ? 1u << tap : 0u;
            d = out ? 0x3f800000u : off ? 0u : d & 0xffff0000u;
            sts32(tab + tv * 384 + tu * 128 + lane * 4, d | ((int)d < 0 ? 0x7654u : 0x3210u));
          }
        }
        if (bad && pv >= 34) push_taps(bars, strip_key(pu, pv, left), bad, offs);
        __syncwarp();
        arrive_if(lane == 0 ? bars + B_SG * 8 : 0u);
      }
      wgmma_fence();
      wgmma_def(acc[1], w_desc(SB), never);
      wgmma_def(acc[0], w_desc(SB), never);
      wgmma_commit();
      wgmma_wait<0>();
      uint32_t la[3];
#pragma unroll
      for (int tv = 0; tv < 3; tv++) {
        const int p = (warp * 4 + ((lane >> 3) & 1)) * 10 + min((lane & 7) + tv, IW - x0);
        la[tv] = sbase + wg * GWIN + p * 64 + ((((lane >> 4) ^ (p >> 1)) & 3) << 4);
      }
      uint32_t D[2][8][2], A[3][8], dl[3][4];
#pragma unroll
      for (int i = 0; i < 6; i++) ldsm4(A[0] + i * 4, tab);
#pragma unroll
      for (int tu = 0; tu < 3; tu++) lds128(dl[tu], tab + tu * 128 + (lane >> 2) * 16);
      auto fetch = [&](int b, uint32_t a) {
#pragma unroll
        for (int i = 0; i < 4; i++) ldsm4(D[b][2 * i][0], D[b][2 * i + 1][0], D[b][2 * i][1], D[b][2 * i + 1][1], (a ^ (((i + b) & 1) * 32)) + i * 2 * GROW);
      };
      mbar_wait(bars + (B_XF + wg * 3) * 8);
      fetch(0, la[0]);
      int tn = 1;
#pragma unroll 1
      for (int st = 0; st < 9; st++) {
        const uint64_t bd = w_desc(SB + SM_GW) + (st < 7 ? st : st - 7) * (STAGE >> 4);
        mbar_wait(bars + (B_WF + st) * 8);
#pragma unroll
        for (int kh = 0; kh < 2; kh++) {
          if (kh && tn == 0) mbar_wait(bars + (B_XF + wg * 3 + (st >= 5 ? 2 : 1)) * 8);
          fetch(kh ^ 1, la[kh]);
          uint32_t E[7][2];
#pragma unroll
          for (int tu = 0; tu < 3; tu++) {
            wgmma_wait<2>();
            keep_alive8(A[tu], nv);
            if (kh == 1 && tu == 0) arrive_if((st == 1 || st == 2) && lane < 2 ? we_addr + st * 8 - 8 : 0u);
#pragma unroll
            for (int i = 0; i < 8; i++) {
              const int r = (i >> 2) * 2 + (i & 1), h = (i >> 1) & 1;
              if (tu == 0 && r == 0) E[0][h] = hsub2(D[kh][1][h], D[kh][0][h]);
              if (tu == 0 || r == 3) E[r + tu + 1][h] = hsub2(D[kh][r + tu + 2][h], D[kh][r + tu + 1][h]);
              A[tu][i] = hfma2_h(dl[tu][r], 1, prmt(E[r + tu + 1][h], E[r + tu][h], dl[tu][r]), D[kh][r + tu + 1][h]);
              if ((i & 3) == 3) {
                wgmma_fence();
                wgmma_rs(acc[i >> 2], A[tu] + (i & 4), bd + tu * WTAP + kh * WHALF, kh + tu ? 1 : st);
              }
            }
            wgmma_commit();
            if (kh) lds128(dl[tu], tab + tn * 384 + tu * 128 + (lane >> 2) * 16);
          }
        }
        const uint32_t l0 = la[0] + (st < 6 ? GSLICE : 0);
        la[0] = la[1];
        la[1] = la[2];
        la[2] = l0;
        tn = tn == 2 ? 0 : tn + 1;
      }
      mbar_wait(bars + B_IM * 8);
      mbar_wait(bars + B_SG * 8);
      uint32_t n0, imp, sel[2];
      lds64(n0, imp, bars + O_CNT);
      lds64(sel[0], sel[1], bars + O_SEL + (lane & 3) * 8);
      wgmma_wait<0>();
#pragma unroll
      for (int i = 0; i < 3; i++) keep_alive8(A[i], nv);
      if (__any_sync(0xffffffffu, (imp >> (wg * 4)) & 1)) {
        const uint32_t code = (wg * 512 + warp * 32 + (lane >> 2) + 0x4000u) * 0x10001u;
        select_rows(A[0], sel, code, false);
        select_rows(A[0] + 4, sel, code + 0x100010u, false);
        wgmma_fence();
        wgmma_rs(acc[0], A[0], w_desc(SB + SM_FIX));
        wgmma_rs(acc[1], A[0] + 4, w_desc(SB + SM_FIX));
        wgmma_commit();
        wgmma_wait<0>();
        keep_alive8(A[0], nv);
      }
      if (__any_sync(0xffffffffu, n0 > NREC || imp >= 0x10000u)) {
        mbar_wait(bars + B_RD * 8);
        ntiles = 2;
        tile0 = left ? wg * 2 + (x0 << 5) : (x0 >> 3) + (wg << 9);
        tstep = left ? 1 : 0x100;
      }
      acc_fence(acc[0]);
      acc_fence(acc[1]);
      bar_sync(1 + wg, 128);
      const uint32_t stg = sbase + wg * GWIN + warp * 2048;
      stage_slab<8192>(acc[0], stg, lane);
      stage_slab<8192>(acc[1], stg + 1024, lane);
      publish(bars + (B_ST + wg * 4) * 8, lane);
    } else {
      ntiles = !wg || cta >= -4;
      tile0 = corner_tile(wg);
      if (!ntiles) {
        arrive_if(lane == 0 ? bars + B_SG * 8 : 0u);
        if (own) {
          const uint32_t key = src < 7 ? wino_key(oy, ox) : strip_key(along, 32 + (t & 1), !lf);
          const uint32_t base = pack2((float)oy, (float)ox), swap = lf ? 0x3210u : 0x1032u, lim = src < 7 ? 0u : 0x3f00u;
          const uint32_t lim0 = along ? lim : 0u, limy = lf ? lim0 : lim, limx = lf ? lim : lim0;
          uint32_t bad = 0;
#pragma unroll
          for (int m = 0; m < 9; m++) {
            const uint32_t gp = hadd2(base, tap_delta(m / 3, m % 3));
            o2[m] = clip2(hadd2(gp, o2[m]));
            bad |= (prmt(hsub2(o2[m], clip2(gp)), 0, swap) & 0x7fff7fffu) > (m == 0 ? lim0 : m < 3 ? limy : m % 3 == 0 ? limx : lim) ? 1u << m : 0u;
          }
#pragma unroll 1
          for (; bad; bad &= bad - 1) {
            const int m = __ffs(bad) - 1;
            uint32_t pos = o2[0];
#pragma unroll
            for (int i = 1; i < 9; i++) pos = m == i ? o2[i] : pos;
            push_record(bars, key | (m << 16), pos);
          }
        }
        bar_sync(2, 128);
        const int n = __shfl_sync(0xffffffffu, lds32(bars + O_CNT), 0);
        if (n && n <= NREC) {
          const uint32_t tmp = sbase + SM_CX + CWIN;
#pragma unroll 1
          for (int i = t; i < n * 12; i += 128) {
            const int r = (i * 171) >> 11;
            uint32_t key, pos, v[4];
            lds64(key, pos, bars + O_REC + r * 8);
            delta(v, key, pos, reinterpret_cast<const uint4*>(x), i - r * 12);
            sts128(tmp + (r + i) * 16, v);
          }
          if (warp == 3) {
#pragma unroll 1
            for (int st = 0; st < 9; st++) mbar_wait(bars + (B_WF + st) * 8);
          }
          bar_sync(2, 128);
          const int r0 = warp ? 99 : lane >> 2;
          const uint32_t k0 = lds32(bars + O_REC + (lane >> 2) * 8), k1 = lds32(bars + O_REC + 64 + (lane >> 2) * 8);
          const uint32_t t0 = r0 < n ? (k0 >> 16) & 15 : 15, t1 = r0 + 8 < n ? (k1 >> 16) & 15 : 15;
          const uint32_t taps = __reduce_or_sync(0xffffffffu, lane < n ? 1u << ((lds32(bars + O_REC + (lane & 15) * 8) >> 16) & 15) : 0u);
          uint32_t D[6][4];
#pragma unroll
          for (int k = 0; k < 6; k++) ldsm4(D[k], tmp + (lane & 15) * 208 + (lane >> 4) * 16 + k * 32);
      wgmma_fence();
      wgmma_def(acc[0], w_desc(SB), never);
      wgmma_commit();
      wgmma_wait<0>();
#pragma unroll 1
          for (uint32_t m = taps; m; m &= m - 1) {
            const uint32_t tap = __ffs(m) - 1, ki = (tap * 11) >> 5;
            uint32_t A[6][4];
#pragma unroll
            for (int k = 0; k < 6; k++) {
#pragma unroll
              for (int i = 0; i < 4; i++) A[k][i] = (i & 1 ? t1 : t0) == tap ? D[k][i] : 0u;
            }
            wgmma_fence();
#pragma unroll
            for (int k = 0; k < 6; k++)
              wgmma_rs(acc[0], A[k], w_desc(SB) + ((k >> 1) * 3 + ki) * (STAGE >> 4) + (tap - ki * 3) * WTAP + (k & 1) * WHALF, k ? 1 : m ^ taps);
            wgmma_commit();
            wgmma_wait<0>();
#pragma unroll
            for (int k = 0; k < 3; k++) keep_alive8(A[2 * k], nv);
          }
          acc_fence(acc[0]);
          if (!warp) {
            uint32_t* dst = reinterpret_cast<uint32_t*>(scr->fix) + src * 768 + (lane >> 2) * 16 + (lane & 3);
#pragma unroll
            for (int j = 0; j < 24; j++) dst[(j >> 3) * 256 + (j & 1) * 128 + ((((j >> 1) ^ (lane >> 3)) & 3) << 2)] = pack2(acc[0][j * 2], acc[0][j * 2 + 1]);
          }
        }
        if (!warp) {
          __threadfence();
          __syncwarp();
          if (lane < NREC)
            asm volatile("st.relaxed.gpu.global.v2.u32 [%0], {%1, %2};\n" ::"l"(scr->key + src * NREC + lane), "r"(lds32(bars + O_REC + lane * 8)),
                         "r"((tag << 8) | min(n, 99)) : "memory");
          if (lane == 0) scr->launch[blockIdx.x] = tag;
        }
      }
    }
    if (ntiles) {
      const uint32_t winb = sbase + SM_CX + wg * CWIN, tab = sbase + SM_CT + wid * 1152;
      const uint32_t ck = (uint32_t)(lane >> 4) << 4, again = tstep != 0;
      if (tstep) {
        bar_sync(3, 256);
        if (wid == 0 && one) {
#pragma unroll 1
          for (int st = 0; st < 9; st++) load_cw(st);
        }
        __syncwarp();
      }
#pragma unroll 1
      for (int n = 0; n < ntiles; n++) {
        const uint32_t tl = tile0 + n * tstep;
        const int wx0 = (int)(tl & 255) * 8 - 2, wy0 = (int)(tl >> 8) * 8 - 2;
        if (tstep && warp == 0 && one) {
#pragma unroll 1
          for (int g = 0; g < 3; g++) load_cx(wg, g, tl);
        }
        __syncwarp();
        uint32_t mout = 0, need = 0, of[5];
        {
          const int ph = wy0 + 2 + 2 * warp + ((lane >> 3) & 1), pw = wx0 + 2 + (lane & 7);
          if (tstep) {
#pragma unroll
            for (int k = 0; k < 5; k++) of[k] = __ldg(offs + (ph * IW + pw) * 9 + min((lane >> 4) + 2 * k, 8));
          } else {
            mbar_wait(bars + B_OG * 8);
#pragma unroll
            for (int k = 0; k < 5; k++) of[k] = lds32(winb + 2 * CSLICE + (warp * 16 + (lane & 15)) * 36 + min((lane >> 4) + 2 * k, 8) * 4);
          }
#pragma unroll 1
          for (int m = lane >> 4; m < 9; m += 2) {
            const int ki = (m * 11) >> 5;
            const uint32_t pos = clip2(hadd2(pack2((float)(ph + ki - 1), (float)(pw + m - ki * 3 - 1)), of[0]));
#pragma unroll
            for (int k = 0; k < 4; k++) of[k] = of[k + 1];
            const uint32_t iy = (int)bf16lo(pos) - wy0, ix = (int)bf16hi(pos) - wx0, f = frac2(pos);
            mout |= max(iy, ix) > 10 ? 1u << m : 0u;
            need |= ((f >> 16 ? 1u : 0u) | (f & 0xffffu ? 0x200u : 0u) | (f >> 16 && f & 0xffffu ? 0x40000u : 0u)) << m;
            const uint32_t pp = (iy * 12 + ix) * 0x10001u + 0x10000u;
            sts32(tab + m * 64 + (lane & 7) * 8 + ((lane >> 1) & 4), f);
            sts32(tab + 576 + m * 64 + (lane & 15) * 4, pp * 64 + ((pp << 3) & 0x300030u));
            of[4] = pos;
          }
          mout = __reduce_or_sync(0xffffffffu, mout);
          need = __reduce_or_sync(0xffffffffu, need);
          arrive_if(lane == 0 && !tstep ? bars + B_SG * 8 : 0u);
        }
        uint32_t outside;
        asm volatile("{\n.reg .pred p, q;\nsetp.ne.u32 p, %1, 0;\nbarrier.red.or.pred q, %2, 128, p;\nselp.u32 %0, 1, 0, q;\n}\n"
                     : "=r"(outside) : "r"(mout), "r"(1 + wg) : "memory");
        outside = __shfl_sync(0xffffffffu, outside, 0);
        wgmma_fence();
        wgmma_def(acc[0], w_desc(SB), never);
        wgmma_commit();
        wgmma_wait<0>();
        if (!outside) {
          uint32_t T[3][4], C[2][3][4];
#pragma unroll
          for (int i = 0; i < 9; i++) ldsm4(i < 3 ? T[i] : C[0][i - 3], tab);
          uint32_t ad[4];
          auto fetch = [&](int k, uint32_t e, uint32_t slice, uint32_t nd) {
            if (!(k & 1)) {
              ad[0] = (e & 0xffffu) + slice;
              ad[1] = (e >> 16) + slice;
              ad[2] = ad[0] ^ 32;
              ad[3] = ad[1] ^ 32;
            }
            ldsm4_if(T[k % 3], ad[(k & 1) * 2], never ^ 1);
            ldsm4_if(C[k & 1][0], ad[(k & 1) * 2 + 1], nd & 1);
            ldsm4_if(C[k & 1][1], ad[2 - (k & 1) * 2] + CROW, nd & 0x200u);
            ldsm4_if(C[k & 1][2], ad[3 - (k & 1) * 2] + CROW, nd & 0x40000u);
          };
          uint32_t ent[3], slice = winb;
          const uint32_t ck2 = ck * 0x10001u;
          mbar_wait(bars + (B_XF + wg * 3) * 8, (n + again) & 1);
          fetch(0, lds32(tab + 576 + (lane & 15) * 4) ^ ck2, slice, need);
          int ki = 0, g = 0;
#pragma unroll 1
          for (int st = 0; st < 9; st++) {
            const uint64_t bd = w_desc(SB) + st * (STAGE >> 4);
            const int kn = ki == 2 ? 0 : ki + 1;
            uint32_t cf[3][4];
#pragma unroll
            for (int j = 0; j < 3; j++) {
              uint32_t wA, wB;
              lds64(wA, wB, tab + (ki * 3 + j) * 64 + (lane >> 2) * 8);
              ent[j] = lds32(tab + 576 + (j < 2 ? ki * 3 + j + 1 : kn * 3) * 64 + (lane & 15) * 4) ^ ck2;
              coefs(wA, cf[j][0], cf[j][1]);
              coefs(wB, cf[j][2], cf[j][3]);
            }
            if (kn == 0 && g < 2) mbar_wait(bars + (B_XF + wg * 3 + g + 1) * 8, (n + again) & 1);
            mbar_wait(bars + (B_WF + st) * 8, again);
#pragma unroll
            for (int k = 0; k < 6; k++) {
              wgmma_wait<1>();
              if (k == 5 && kn == 0 && g < 2) {
                g++;
                slice += CSLICE;
              }
              fetch(k + 1, ent[k >> 1], slice, need >> (k < 5 ? ki * 3 + ((k + 1) >> 1) : kn * 3));
              blend4(T[k % 3], C[k & 1][0], C[k & 1][1], C[k & 1][2], cf[k >> 1][0], cf[k >> 1][1], cf[k >> 1][2], cf[k >> 1][3]);
              wgmma_fence();
              wgmma_rs(acc[0], T[k % 3], bd + (k >> 1) * WTAP + (k & 1) * WHALF, k ? 1 : st);
              wgmma_commit();
            }
            ki = kn;
          }
          wgmma_wait<0>();
          keep_alive8(T[0], nv);
          keep_alive8(T[1], nv);
        } else {
#pragma unroll
          for (int k = 0; k < 5; k++) {
            const int m = 2 * k - (lane >> 4);
            if (m >= 0) sts32(tab + m * 64 + (lane & 7) * 8 + ((lane >> 1) & 4), of[k]);
          }
          __syncwarp();
          uint32_t buf[2][8];
#pragma unroll
          for (int i = 0; i < 16; i++) buf[0][i] = nv;
          const uint32_t tmp = tab + 576 + lane * 16;
          int tap = 0, g = 0;
#pragma unroll 1
          for (int d = 0;; d += 2) {
#pragma unroll
            for (int b = 0; b < 2; b++) {
              const int k = d + b, q = (k * 11) >> 5;
              if (k == 27) goto tile_done;
              mbar_wait(bars + (B_XF + wg * 3 + g) * 8, (n + again) & 1);
              mbar_wait(bars + (B_WF + q) * 8, again);
              const uint32_t pos = lds32(tab + tap * 64 + (lane & 7) * 8 + ((lane >> 1) & 4));
              const int gy = (int)bf16lo(pos), gx = (int)bf16hi(pos);
              uint32_t T[8];
              if (!((mout >> tap) & 1)) {
                uint32_t wA, wB, pA0, pA1, pB0, pB1, G[4], H[4], K[4];
                lds64(wA, wB, tab + tap * 64 + (lane >> 2) * 8);
                const uint32_t slice = winb + g * CSLICE;
                const uint32_t p = (gy - wy0) * 12 + gx - wx0, p1 = p + 1;
                const uint32_t a00 = slice + p * 64 + (((p << 3) & 0x30) ^ ck), a01 = slice + p1 * 64 + (((p1 << 3) & 0x30) ^ ck);
                coefs(frac2(wA), pA0, pA1);
                coefs(frac2(wB), pB0, pB1);
#pragma unroll
                for (int hf = 0; hf < 2; hf++) {
                  ldsm4(T + hf * 4, a00 ^ (hf * 32));
                  ldsm4(G, a01 ^ (hf * 32));
                  ldsm4(H, (a00 + CROW) ^ (hf * 32) ^ 32);
                  ldsm4(K, (a01 + CROW) ^ (hf * 32) ^ 32);
                  blend4(T + hf * 4, G, H, K, pA0, pA1, pB0, pB1);
                }
              } else {
                uint32_t q0, q1;
                coefs(frac2(pos), q0, q1);
                const int sx = gx < IW - 1 ? IC / 8 : 0, sy = gy < IH - 1 ? IW * IC / 8 : 0;
                const uint4* pc = reinterpret_cast<const uint4*>(x) + (gy * IW + gx) * (IC / 8) + g * 4 + (lane >> 4);
#pragma unroll
                for (int hf = 0; hf < 2; hf++) {
                  uint4 v[4];
                  v[0] = __ldg(pc + hf * 2);
                  v[1] = __ldg(pc + hf * 2 + sx);
                  v[2] = __ldg(pc + hf * 2 + sy);
                  v[3] = __ldg(pc + hf * 2 + sy + sx);
                  blend4(&v[0].x, &v[1].x, &v[2].x, &v[3].x, q0, q1, q0, q1);
                  __syncwarp();
                  sts128(tmp, &v[0].x);
                  __syncwarp();
                  ldsm4(T + hf * 4, tmp);
                }
              }
              wgmma_wait<1>();
              keep_alive8(buf[b], nv);
#pragma unroll
              for (int i = 0; i < 8; i++) asm volatile("xor.b32 %0, %1, %2;\n" : "=r"(buf[b][i]) : "r"(T[i]), "r"(nv));
              const uint64_t bd = w_desc(SB) + q * (STAGE >> 4) + (k - q * 3) * WTAP;
              wgmma_fence();
              wgmma_rs(acc[0], buf[b], bd, k);
              wgmma_rs(acc[0], buf[b] + 4, bd + WHALF);
              wgmma_commit();
              if (++tap == 9) {
                tap = 0;
                g++;
              }
            }
          }
        tile_done:
          wgmma_wait<0>();
          keep_alive8(buf[0], nv);
          keep_alive8(buf[1], nv);
        }
        acc_fence(acc[0]);
        bar_sync(1 + wg, 128);
        stage_slab(acc[0], winb + warp * 1024, lane);
        fence_async();
        bar_sync(1 + wg, 128);
        if (warp == 0 && one) {
          tma_store(&tm.out[3], winb, wx0 + 2, wy0 + 2, 0);
          asm volatile("cp.async.bulk.wait_group.read 0;\n" ::: "memory");
        }
      }
    }
  } else if (wid < 12) {
    asm volatile("setmaxnreg.dec.sync.aligned.u32 40;\n");
    if (prep) {
      const int lane = lane_now();
      uint32_t u[4][4];
      weights4<true>(&g[0].x, &g[1].x, &g[2].x, u);
      const uint8_t* udst = scr->u + ((cta >> 2) & 1) * (4 * STAGE) + (cta & 2) * (STAGE / 4) + ((cta - NW) >> 3) * 3072 + (wid - 8) * 1024 +
                            (cta & 1) * 512 + (lane >> 2) * 64 + (((lane ^ (lane >> 3)) & 3) << 4);
#pragma unroll
      for (int k = 0; k < 4; k++)
        asm volatile("st.relaxed.gpu.global.v4.b32 [%0], {%1, %2, %3, %4};\n" ::"l"(udst + k * STAGE), "r"(u[k][0]), "r"(u[k][1]), "r"(u[k][2]), "r"(u[k][3]) : "memory");
      uint32_t chk = 0;
#pragma unroll
      for (int k = 0; k < 4; k++) {
        uint32_t v;
        asm volatile("ld.relaxed.gpu.global.b32 %0, [%1];\n" : "=r"(v) : "l"(udst + k * STAGE) : "memory");
        chk |= v;
      }
      chk = __reduce_or_sync(0xffffffffu, chk & never);
      if (one) asm volatile("red.relaxed.gpu.global.add.u32 [%0], %1;\n" ::"l"(scr->cnt), "r"(chk + 1) : "memory");
    }
    asm volatile("barrier.cluster.wait.acquire.aligned;\n" ::: "memory");
    const int w = wid - 8, lane = lane_now();
    uint32_t asked = 1;
    if (wino) {
      bar_sync(12, 384);
      arrive_if(one ? bars + (B_WF + w) * 8 : 0u);
      const int hi = w >> 1, ty = (w & 1) * 4 + (lane >> 4) * 2;
      const bool bottom = y0 + 4 * ty + 8 == IH;
      uint32_t d0[4][2], dm[2][2][2], d1[4][2];
      auto fetch0 = [&](int e, uint32_t src, bool low) {
#pragma unroll
        for (int r = 0; r < 4; r++) lds64(d0[r][0], d0[r][1], src + r * 128);
        lds64(dm[e][0][0], dm[e][0][1], src + 4 * 128);
        lds64(dm[e][1][0], dm[e][1][1], src + (low && bottom ? 4 * 128 : 5 * 128));
      };
      uint32_t src = sbase + SM_R + hi * PIECE + ty * 512 + (lane & 15) * 8;
      uint32_t v0 = sbase + ty * VROW + hi * 128 + (lane & 8) * 8 + (lane & 1) * 8 + ((((lane >> 1) ^ (ty + hi)) & 3) << 4);
      const uint32_t x1 = hi ? 48 : 16;
      mbar_wait(bars + (B_XF + 2) * 8);
      fetch0(0, src + 4 * VSLOT - SM_R + (4 - hi) * PIECE + hi * 512, hi);
      transform6<2>(d0, d0 + 2, dm[0], v0 + 512 + hi * (VROW - 128), 10 * VSLOT);
      publish(bars + B_V0 * 8, !one);
      mbar_wait(bars + B_V0 * 8);
      mbar_wait(bars + (B_VF + 1) * 8);
      v0 += 4 * VSLOT;
#pragma unroll 1
      for (int s = 0; s < 2; s++) {
        const uint32_t xf = bars + (B_XF + 5 + s * 5) * 8, off0 = s ? 12 * VSLOT : 4 * VSLOT;
        if (s) mbar_wait(bars + B_VE * 8);
        mbar_wait(xf);
        fetch0(0, src, false);
#pragma unroll 1
        for (int jj = 0; jj < 4; jj += 2) {
          asm volatile("" : "+r"(src), "+r"(v0));
#pragma unroll
          for (int e = 0; e < 2; e++) {
            const int j = jj + e;
            const uint32_t ready = mbar_poll(xf + j * 8 + 8);
#pragma unroll
            for (int r = 0; r < 3; r++) lds64(d1[r][0], d1[r][1], src + e * 2 * PIECE + (6 + r) * 128);
            lds64(d1[3][0], d1[3][1], src + e * 2 * PIECE + (bottom ? 8 * 128 : 9 * 128));
            transform6<2>(d0, d0 + 2, dm[e], (v0 ^ e * 32) + e * 256, off0);
            if (!ready) mbar_wait(xf + j * 8 + 8);
            fetch0(e ^ 1, (src + ((e + 1) * 2 * PIECE - (j == 3 ? hi * (PIECE - 512) : 0))) & (j == 3 && x0 + 16 == IW ? ~64u : ~0u), j == 3 && hi);
            transform6<2>(dm[e], d1, d1 + 2, (v0 ^ x1 ^ e * 32) + e * 256 + VROW, off0);
            __syncwarp();
            arrive_if(one && (!s || j == 2) ? bars + (B_RE + j + s * 3) * 8 : 0u);
            if (j + hi == 2) publish(bars + (B_VF + 2 + s * 2) * 8, !one);
          }
          src += 4 * PIECE;
          v0 += 512;
        }
        transform6<2>(d0, d0 + 2, dm[0], v0 + hi * (VROW - 128), off0);
        publish(bars + (B_VF + 3 + s * 2) * 8, !one);
        arrive_if(one && !s ? bars + (B_RE + 4) * 8 : 0u);
        v0 -= 4 * VSLOT + 1024;
        src -= 8 * PIECE;
      }
      mbar_wait(bars + B_OF * 8);
      uint32_t mx = 0;
#pragma unroll
      for (int h = 0; h < 2; h++) {
        uint32_t v[6][4];
#pragma unroll
        for (int k = 0; k < 6 - 3 * h; k++) lds128(v[k], sbase + SM_R + w * 4608 + (h * 6 + k) * 512 + lane * 16);
#pragma unroll
        for (int k = 0; k < 6 - 3 * h; k++) mx = absmax2(mx, absmax2(absmax2(v[k][0], v[k][1]), absmax2(v[k][2], v[k][3])));
      }
      const uint32_t lim = (pack2((float)max(y0, 34) - 1.5f, (float)max(x0, 34) - 1.5f) & 0x7f807f80u) - 0x04000400u;
      uint32_t who = __ballot_sync(0xffffffffu, (mx & 0x7fffu) >= (lim & 0xffffu) || (mx & 0x7fff0000u) >= (lim & 0xffff0000u));
      asm volatile("{\n.reg .pred p, q;\nsetp.ne.u32 p, %1, 0;\nbarrier.red.or.pred q, 4, 128, p;\nselp.u32 %0, 1, 0, q;\n}\n"
                   : "=r"(asked) : "r"(who) : "memory");
      arrive_if(!asked && w == 0 && one ? bars + B_RD * 8 : 0u);
#pragma unroll 1
      for (; who; who &= who - 1) {
#pragma unroll 1
        for (int k = lane; k < 64; k += 32) {
          const int wd = (k >> 2) * 128 + (__ffs(who) - 1) * 4 + (k & 3), c = (wd * 7282) >> 16, tap = wd - c * 9, ki = (tap * 11) >> 5;
          const int y = y0 + w * 8 + (c >> 4), xx = x0 + (c & 15);
          if (k < 36 && min(y, xx) >= 34) {
            const uint32_t gp = pack2((float)(y + ki - 1), (float)(xx + tap - ki * 3 - 1));
            const uint32_t pos = clip2(hadd2(gp, lds32(sbase + SM_R + w * 4608 + wd * 4)));
            if (pos != clip2(gp)) push_record(bars, wino_key(y, xx) | (tap << 16), pos);
          }
          __syncwarp();
        }
      }
      bar_sync(4, 128);
    }
    if (wino || strip) {
      if (strip) mbar_wait(bars + B_SG * 8);
      const uint32_t n0 = __shfl_sync(0xffffffffu, lds32(bars + O_CNT), 0);
      if (n0 <= NREC) fixup(bars, w, n0, reinterpret_cast<const uint4*>(x), wgt);
      if (w == 0) {
        arrive_if(one && asked ? bars + B_RD * 8 : 0u);
        mbar_wait(bars + B_IM * 8);
        if (one) atomicAdd(scr->launch + blockIdx.x, 1);
      }
    }
  } else {
    asm volatile("setmaxnreg.dec.sync.aligned.u32 24;\n");
    asm volatile("barrier.cluster.wait.acquire.aligned;\n" ::: "memory");
    auto wait_all = [&](uint32_t dt) {
      while (__shfl_sync(0xffffffffu, clock32(), 0) - tstart < dt) __nanosleep(40);
    };
    if (wid == 15 && !wino) {
      const uint32_t dst = sbase + (strip ? SM_GW : 0) + (cta & 1) * (STAGE / 2);
      int g = 0, r = 0;
#pragma unroll 1
      for (int k = 0; k < 9; k++) {
        if (strip && k >= 7) mbar_wait(bars + (B_WE + k - 7) * 8);
        else wait_all(strip ? GW0 + k * GWS : CW0 + k * CWS);
        if (one) {
          mbar_expect_tx(bars + (B_WF + k) * 8, STAGE);
          tma_load_w(dst + (strip && k >= 7 ? k - 7 : k) * STAGE, &tm.w[left], bars + (B_WF + k) * 8, g + (cta & 1) * 16, left ? 0 : r, left ? r : 0, 3);
        }
        if (++r == 3) {
          r = 0;
          g += 32;
        }
      }
    }
    if (wid >= 13 && wid < 15 && !wino) {
      const int r = 14 - wid;
      const uint32_t tl = corner_tile(r);
#pragma unroll 1
      for (int g = 0; g < 3; g++) {
        if (g == 2) mbar_wait(bars + B_SG * 8);
        wait_all(strip ? (r ? GX1 + g * GXS1 : GX0 + g * GXS + (g >> 1) * GXE) : CX0 + g * CXS);
        if (one && (strip || (g && (!r || cta >= -4))))
          tma_load_x(sbase + (strip ? r * GWIN + g * GSLICE : SM_CX + r * CWIN + g * CSLICE), &tm.x[strip ? 1 + left : 3],
                     bars + (B_XF + r * 3 + g) * 8, strip ? GSLICE : CSLICE, g * 32, strip ? x0 - 1 : (int)(tl & 255) * 8 - 2,
                     strip ? r * 16 - 2 : (int)(tl >> 8) * 8 - 2);
      }
    }
    if (wid == 15) {
      if (wino) {
        wait_all(PDELAY);
        asm volatile(
            "{\n.reg .pred p;\n.reg .u32 n, v;\nmov.u32 n, 0;\n"
            "W_%=:\n"
            "ld.relaxed.gpu.global.u32 v, [%0];\nsetp.ge.u32 p, v, 72;\nvote.sync.all.pred p, p, 0xffffffff;\n"
            "@p bra D_%=;\n"
            "add.u32 n, n, 1;\nsetp.lt.u32 p, n, 0x100000;\n@p bra W_%=;\ntrap;\n"
            "D_%=:\nfence.proxy.async.global;\n}\n" ::"l"(scr->cnt)
            : "memory");
#pragma unroll 1
        for (int k = 0; k < 8; k++) {
          mbar_wait(bars + (B_WE + ((0x77654210u >> (4 * k)) & 15)) * 8);
          if (one)
            bulk_load_mc(sbase + (uint32_t)((w_slots(4, 1, 8) >> (8 * k)) & 255) * 1024 + (cta & 1) * (STAGE / 2),
                         scr->u + (k * 2 + (cta & 1)) * (STAGE / 2), STAGE / 2, bars + (B_WF + 4 + k) * 8);
        }
        if (one) atomicInc(scr->cnt, 72 + NW - 1);
#pragma unroll
        for (int k = 0; k < 6; k++) {
          if (k > 0 && k < 5) mbar_wait(bars + (B_WE + min(7 + k, 11)) * 8);
          if (one)
            tma_load_w(sbase + (uint32_t)((w_slots(12, 1, 6) >> (8 * k)) & 255) * 1024 + (cta & 1) * (STAGE / 2), &tm.w[1],
                       bars + (B_WF + 12 + k) * 8, (k < 3 ? k : k - 3) * 32 + (cta & 1) * 16, 0, k < 3 ? 0 : 2, 3);
        }
      }
    } else if (wid == 14) {
      if (wino) {
#pragma unroll 1
        for (int s = 1; s < 3; s++) {
#pragma unroll
          for (int j = 0; j < 5; j++) {
            if (s == 2) mbar_wait(bars + (B_RE + j) * 8);
            else if (j == 0 || j == 2) wait_all(j ? SDELAY + SDELAY2 : SDELAY);
            if (one) load_cols(s, j);
          }
        }
      }
    } else if (wino || strip) {
      const int wg = wid - 12;
      if (one) {
        if (wino && wg) {
#pragma unroll 1
          for (int i = 4; i < 18; i++) mbar_expect_tx(bars + (B_WF + i) * 8, STAGE);
        } else if (wino) {
#pragma unroll 1
          for (int i = 0; i < 15; i++) mbar_expect_tx(bars + (B_XF + i) * 8, (0x4210 >> i) & 1 ? PIECE : 2 * PIECE);
        }
        asm volatile("prefetch.tensormap [%0];\n" ::"l"(reinterpret_cast<uint64_t>(&tm.out[wino ? 0 : 1 + left])) : "memory");
      }
      if (wino && !wg) {
        if (one) {
          wait_until(tstart, FDELAY);
          asm volatile("cp.async.bulk.prefetch.tensor.2d.L2.global [%0, {%1, %2}];\n" ::"l"(reinterpret_cast<uint64_t>(&tm.o[0])), "r"(x0 * 9), "r"(y0) : "memory");
          mbar_expect_tx(bars + B_OF * 8, 2 * VSLOT);
          mbar_wait(bars + B_R2 * 8);
          tma_load_o(sbase + SM_R, &tm.o[0], bars + B_OF * 8, x0, y0);
        }
        bar_sync(7, 32);
      }
      if (wg == wino) {
        bar_sync(6, 32);
        const int lane = lane_now();
        const uint32_t tag = scr->launch[blockIdx.x] + 1;
        uint32_t n = 0;
        if (x0 == 32 || (wino && y0 == 32)) {
          wait_all(IDELAY);
          const int src = !wino ? 7 : ry ? (ry + 7) >> 1 : (0xfea550u >> (2 * cta)) & 3;
          uint32_t key, v;
          asm volatile(
              "{\n.reg .pred p;\n.reg .u32 n, t;\nmov.u32 n, 0;\n"
              "W_%=:\n"
              "ld.acquire.gpu.global.v2.u32 {%0, %1}, [%2];\nxor.b32 t, %1, %3;\nsetp.lt.u32 p, t, 256;\nvote.sync.all.pred p, p, 0xffffffff;\n"
              "@p bra D_%=;\n"
              "nanosleep.u32 100;\nadd.u32 n, n, 1;\nsetp.lt.u32 p, n, 0x100000;\n@p bra W_%=;\ntrap;\n"
              "D_%=:\nfence.proxy.async.global;\n}\n"
              : "=r"(key), "=r"(v)
              : "l"(scr->key + src * NREC + (lane & 15)), "r"(tag << 8)
              : "memory");
          v &= 255;
          const uint32_t dy = (key & 255) - (wino ? y0 : left ? 32 : 0), dx = ((key >> 8) & 255) - (wino || !left ? x0 : 0);
          const bool mine = lane < v && dy < 32 && dx < (left ? 32 : 16);
          n = __reduce_or_sync(0xffffffffu, v > NREC ? 0x10000u : mine ? 1u << (key >> 27) : 0u);
          put_sel(bars, mine ? key : ~0u, lane);
          if (n && n < 256 && one) {
            asm volatile("mbarrier.expect_tx.relaxed.cta.shared::cta.b64 [%0], 3072;\n" ::"r"(bars + B_IM * 8) : "memory");
            asm volatile("cp.async.bulk.shared::cluster.global.mbarrier::complete_tx::bytes [%0], [%1], 3072, [%2];\n" ::"r"(sbase + SM_FIX),
                         "l"(scr->fix + src * 192), "r"(bars + B_IM * 8) : "memory");
          }
          __syncwarp();
        }
        if (lane == 0) sts32(bars + O_CNT + 4, n + (tag & never));
        __syncwarp();
        arrive_if(lane == 0 ? bars + B_IM * 8 : 0u);
      }
      mbar_wait(bars + B_IM * 8);
      mbar_wait(bars + B_RD * 8);
      uint32_t n0, imp;
      lds64(n0, imp, bars + O_CNT);
      if (__all_sync(0xffffffffu, n0 <= NREC && imp < 0x10000u)) {
        const int lane = lane_now();
        const uint32_t key = lane < n0 ? lds32(bars + O_REC + lane * 8) : ~0u;
        const CUtensorMap* map = &tm.out[wino ? 0 : 1 + left];
        const int c1 = x0 + (wino ? wg * 8 : 0), c3 = wino ? y0 >> 2 : 0;
#pragma unroll 1
        for (int i = wino ? 2 : 0;; i = (i - 1) & 3) {
          const uint32_t stg = sbase + (wino ? w_stg(wg, i) : wg * GWIN), sb = bars + (B_ST + wg * 4 + i) * 8;
          uint32_t mask = __ballot_sync(0xffffffffu, key >> 27 == wg * 4 + i);
          if (mask) {
#pragma unroll 1
            do {
              const uint32_t r = __ffs(mask) - 1, m = (__shfl_sync(0xffffffffu, key, r) >> 20) & 127, l = min(lane, 23);
              const uint32_t a = stg + (l >> 3) * (wino ? 4096 : 8192) + m * 64 + ((((l ^ m) >> 1) & 3) << 4) + (l & 1) * 8;
              uint32_t v[2], c[2];
              lds64(c[0], c[1], sbase + SM_FIX + 3072 + r * 192 + l * 8);
              mbar_wait(sb);
              lds64(v[0], v[1], a);
              v[0] = hadd2(v[0], c[0]);
              v[1] = hadd2(v[1], c[1]);
              sts64(a, v);
              mask &= mask - 1;
            } while (mask);
            fence_async();
            __syncwarp();
          }
          mbar_wait(sb);
          if (one) tma_store(map, stg, c1, wino ? i : wg * 16, c3);
          if (!wg && wino && i < 2) {
            asm volatile("cp.async.bulk.wait_group.read 1;\n" ::: "memory");
            arrive_if(one ? bars + (B_SR + 1 - i) * 8 : 0u);
          }
          if (i == 3 || !wino) break;
        }
        asm volatile("cp.async.bulk.wait_group.read 0;\n" ::: "memory");
      } else {
        arrive_if(one ? bars + (B_SR + wg) * 8 : 0u);
      }
    }
  }
}

typedef CUresult (*EncodeTiledFn)(CUtensorMap*, CUtensorMapDataType, cuuint32_t, void*, const cuuint64_t*,
                                  const cuuint64_t*, const cuuint32_t*, const cuuint32_t*, CUtensorMapInterleave,
                                  CUtensorMapSwizzle, CUtensorMapL2promotion, CUtensorMapFloatOOBfill);

}

extern "C" void kernel_launch(void* const* d_in, const int* in_sizes, int n_in, void* d_out, int out_size) {
  static EncodeTiledFn encode = nullptr;
  static void* scratch = nullptr;
  if (!encode) {
    cudaGetSymbolAddress(&scratch, g_scratch);
    void* fn = nullptr;
    cudaDriverEntryPointQueryResult qres;
    cudaGetDriverEntryPoint("cuTensorMapEncodeTiled", &fn, cudaEnableDefault, &qres);
    encode = (EncodeTiledFn)fn;
    cudaFuncSetAttribute(dcn_kernel, cudaFuncAttributeMaxDynamicSharedMemorySize, SMEM_BYTES);
  }
  Maps tm;
  const cuuint32_t es[5] = {1, 1, 1, 1, 1};
  constexpr cuuint64_t PX = IC * 2, ROW = IW * IC * 2;
  for (int i = 0; i < 4; i++) {
    const cuuint64_t dims[3] = {IC, IW, IH};
    const cuuint64_t strides[2] = {i == 2 ? ROW : PX, i == 2 ? PX : ROW};
    const cuuint32_t box[4][3] = {{32, 2, 34}, {32, 10, 20}, {32, 10, 20}, {32, 12, 12}};
    encode(&tm.x[i], CU_TENSOR_MAP_DATA_TYPE_BFLOAT16, 3, d_in[0], dims, strides, box[i], es, CU_TENSOR_MAP_INTERLEAVE_NONE,
           i ? CU_TENSOR_MAP_SWIZZLE_64B : CU_TENSOR_MAP_SWIZZLE_NONE, CU_TENSOR_MAP_L2_PROMOTION_NONE,
           CU_TENSOR_MAP_FLOAT_OOB_FILL_NONE);
  }
  {
    const cuuint64_t dims[4] = {IC, 2, IH, IW / 2 - 1};
    const cuuint64_t strides[3] = {PX, ROW, 2 * PX};
    const cuuint32_t box[4] = {32, 2, 34, 2};
    encode(&tm.x[4], CU_TENSOR_MAP_DATA_TYPE_BFLOAT16, 4, (char*)d_in[0] + PX, dims, strides, box, es, CU_TENSOR_MAP_INTERLEAVE_NONE,
           CU_TENSOR_MAP_SWIZZLE_NONE, CU_TENSOR_MAP_L2_PROMOTION_NONE, CU_TENSOR_MAP_FLOAT_OOB_FILL_NONE);
  }
  for (int i = 0; i < 2; i++) {
    const cuuint64_t dims[5] = {32, IC, 3, 3, 3};
    const cuuint64_t strides[4] = {IC * 2, 64, IC * IC * 2, 3 * IC * IC * 2};
    const cuuint32_t box[5] = {32, 16, 3, i ? 3u : 1u, i ? 1u : 3u};
    encode(&tm.w[i], CU_TENSOR_MAP_DATA_TYPE_BFLOAT16, 5, d_in[2], dims, strides, box, es, CU_TENSOR_MAP_INTERLEAVE_NONE,
           CU_TENSOR_MAP_SWIZZLE_64B, CU_TENSOR_MAP_L2_PROMOTION_L2_128B, CU_TENSOR_MAP_FLOAT_OOB_FILL_NONE);
  }
  for (int i = 0; i < 2; i++) {
    const cuuint64_t dims[2] = {IW * 9, IH};
    const cuuint64_t strides[1] = {IW * 36};
    const cuuint32_t box[2] = {i ? 72u : 144u, i ? 8u : 32u};
    encode(&tm.o[i], CU_TENSOR_MAP_DATA_TYPE_UINT32, 2, d_in[1], dims, strides, box, es, CU_TENSOR_MAP_INTERLEAVE_NONE,
           CU_TENSOR_MAP_SWIZZLE_NONE, CU_TENSOR_MAP_L2_PROMOTION_NONE, CU_TENSOR_MAP_FLOAT_OOB_FILL_NONE);
  }
  for (int i = 0; i < 4; i++) {
    const cuuint64_t dims[5] = {32, IW, i ? IH : 4u, i ? 1u : IH / 4, 3};
    const cuuint64_t strides[4] = {i == 2 ? ROW : PX, i == 2 ? PX : ROW, 4 * ROW, 64};
    const cuuint32_t box[5] = {32, 8, i == 3 ? 8u : i ? 16u : 1u, i ? 1u : 8u, 3};
    encode(&tm.out[i], CU_TENSOR_MAP_DATA_TYPE_BFLOAT16, 5, d_out, dims, strides, box, es, CU_TENSOR_MAP_INTERLEAVE_NONE,
           CU_TENSOR_MAP_SWIZZLE_64B, CU_TENSOR_MAP_L2_PROMOTION_NONE, CU_TENSOR_MAP_FLOAT_OOB_FILL_NONE);
  }
  dcn_kernel<<<GRID, NTHREADS, SMEM_BYTES>>>((const __nv_bfloat16*)d_in[0], (const uint32_t*)d_in[1], (const uint4*)d_in[2],
                                             (Scratch*)scratch, 0u, tm);
}
```

```cpp
#include <cuda_runtime.h>
#include <cuda.h>
#include <cuda_bf16.h>
#include <stdint.h>

namespace {

constexpr int IH = 224, IW = 224, IC = 96;
constexpr int GRID = 132, NC = 12, NW = 72, NG = 48;
constexpr int NTHREADS = 512;
constexpr int STAGE = 18432;
constexpr int WTAP = 3072 >> 4, WHALF = (STAGE / 2) >> 4;
constexpr uint32_t SB = 0x400;
constexpr int VROW = 18 * 64, VSLOT = 8 * VROW, PIECE = 34 * 128;
constexpr int SM_R = 14 * VSLOT, SM_WW = SM_R + 39936;
constexpr int GROW = 10 * 64, GSLICE = 20 * GROW, GWIN = 3 * GSLICE, SM_GW = 2 * GWIN, SM_GO = SM_GW + 7 * STAGE, SM_GT = SM_GO + 9216;
constexpr int CROW = 12 * 64, CSLICE = 12 * CROW, CWIN = 3 * CSLICE, SM_CX = 9 * STAGE, SM_CT = SM_CX + 2 * CWIN;
constexpr int SM_FIX = 224256, SM_BAR = 231168, SMEM_BYTES = 232448;
constexpr int B_XF = 0;
constexpr int B_OG = 7;
constexpr int B_WF = 16;
constexpr int B_IM = 34;
constexpr int B_OF = 35;
constexpr int B_SR = 36;
constexpr int B_FX = 38;
constexpr int B_RD = 39;
constexpr int B_W2 = 96;
constexpr int B_WE = 40;
constexpr int B_WL = 56;
constexpr int B_V0 = 57;
constexpr int B_SG = 58;
constexpr int B_VE = 59;
constexpr int B_VB = 59;
constexpr int B_ST = 64;
constexpr int B_VF = 71;
constexpr int B_RE = 80;
constexpr int B_R2 = 85;
constexpr int B_PP = 86;
constexpr int O_CNT = 776, O_REC = 784, O_SEL = 912;
constexpr int NREC = 16;
constexpr uint32_t SDELAY = 3000, SDELAY2 = 500, PDELAY = 5200, FDELAY = 9500, IDELAY = 8000;
constexpr uint32_t GX0 = 1500, GXS = 2000, GXE = 1500, GX1 = 4000, GXS1 = 3700, GW0 = 1600, GWS = 850;
constexpr uint32_t CX0 = 1000, CXS = 2200, CW0 = 1000, CWS = 450;

struct Scratch {
  uint8_t u[8 * STAGE];
  uint4 fix[8 * NREC * 12];
  uint2 key[8 * NREC];
  uint32_t cnt[32];
  uint32_t launch[160];
};
__device__ __align__(128) Scratch g_scratch;

__device__ __forceinline__ float bf16lo(uint32_t v) { return __uint_as_float(v << 16); }
__device__ __forceinline__ float bf16hi(uint32_t v) { return __uint_as_float(v & 0xffff0000u); }
__device__ __forceinline__ uint32_t smem_u32(const void* p) { return (uint32_t)__cvta_generic_to_shared(p); }
__device__ __forceinline__ void mbar_init(uint32_t bar, uint32_t count) {
  asm volatile("mbarrier.init.shared::cta.b64 [%0], %1;\n" ::"r"(bar), "r"(count) : "memory");
}
__device__ __forceinline__ void mbar_expect_tx(uint32_t bar, uint32_t bytes) {
  asm volatile("mbarrier.arrive.expect_tx.shared::cta.b64 _, [%0], %1;\n" ::"r"(bar), "r"(bytes) : "memory");
}
__device__ __forceinline__ void mbar_wait(uint32_t bar, uint32_t parity = 0) {
  asm volatile(
      "{\n.reg .pred p;\n"
      "W_%=:\n"
      "mbarrier.try_wait.parity.shared::cta.b64 p, [%0], %1;\n"
      "@!p bra W_%=;\n}\n"
      ::"r"(bar), "r"(parity) : "memory");
}
__device__ __forceinline__ uint32_t mbar_poll(uint32_t bar) {
  uint32_t done;
  asm volatile(
      "{\n.reg .pred p;\n"
      "mbarrier.test_wait.parity.shared::cta.b64 p, [%1], 0;\n"
      "selp.u32 %0, 1, 0, p;\n}\n"
      : "=r"(done)
      : "r"(bar)
      : "memory");
  return done;
}
__device__ __forceinline__ uint32_t clock32() {
  uint32_t c;
  asm volatile("mov.u32 %0, %%clock;\n" : "=r"(c)::"memory");
  return c;
}
__device__ __forceinline__ int lane_now() {
  int l;
  asm volatile("mov.u32 %0, %%laneid;\n" : "=r"(l));
  return l;
}
__device__ __forceinline__ void wait_until(uint32_t t0, uint32_t dt) {
  while (clock32() - t0 < dt) __nanosleep(40);
}
__device__ __forceinline__ void tma_load_x(uint32_t dst, const CUtensorMap* tm, uint32_t bar, uint32_t bytes, int c0, int c1, int c2) {
  if (bytes) mbar_expect_tx(bar, bytes);
  asm volatile(
      "cp.async.bulk.tensor.3d.shared::cluster.global.mbarrier::complete_tx::bytes [%0], [%1, {%3, %4, %5}], [%2];\n" ::"r"(dst),
      "l"(reinterpret_cast<uint64_t>(tm)), "r"(bar), "r"(c0), "r"(c1), "r"(c2)
      : "memory");
}
__device__ __forceinline__ void tma_load_x4(uint32_t dst, const CUtensorMap* tm, uint32_t bar, int c, int y, int pair) {
  asm volatile(
      "cp.async.bulk.tensor.4d.shared::cluster.global.mbarrier::complete_tx::bytes [%0], [%1, {%3, %6, %4, %5}], [%2];\n" ::"r"(dst),
      "l"(reinterpret_cast<uint64_t>(tm)), "r"(bar), "r"(c), "r"(y), "r"(pair), "r"(0)
      : "memory");
}
__device__ __forceinline__ void tma_load_o(uint32_t dst, const CUtensorMap* tm, uint32_t bar, int x, int y) {
  asm volatile(
      "cp.async.bulk.tensor.2d.shared::cluster.global.mbarrier::complete_tx::bytes [%0], [%1, {%3, %4}], [%2];\n" ::"r"(dst),
      "l"(reinterpret_cast<uint64_t>(tm)), "r"(bar), "r"(x * 9), "r"(y)
      : "memory");
}
__device__ __forceinline__ void tma_load_w(uint32_t dst, const CUtensorMap* tm, uint32_t bar, int c, int kj, int ki, uint32_t mask) {
  asm volatile(
      "cp.async.bulk.tensor.5d.shared::cluster.global.mbarrier::complete_tx::bytes.multicast::cluster [%0], [%1, {%3, %4, "
      "%3, %5, %6}], [%2], %7;\n" ::"r"(dst),
      "l"(reinterpret_cast<uint64_t>(tm)), "r"(bar), "r"(0), "r"(c), "r"(kj), "r"(ki), "h"((uint16_t)mask)
      : "memory");
}
__device__ __forceinline__ void bulk_load_mc(uint32_t dst, const void* src, uint32_t bytes, uint32_t bar) {
  asm volatile(
      "cp.async.bulk.shared::cluster.global.mbarrier::complete_tx::bytes.multicast::cluster [%0], [%1], %2, [%3], %4;\n" ::"r"(dst),
      "l"(src), "r"(bytes), "r"(bar), "h"((uint16_t)3)
      : "memory");
}
__device__ __forceinline__ void tma_store(const CUtensorMap* tm, uint32_t src, int c1, int c2, int c3) {
  asm volatile("cp.async.bulk.tensor.5d.global.shared::cta.bulk_group [%0, {%2, %3, %4, %5, %2}], [%1];\n" ::"l"(
                   reinterpret_cast<uint64_t>(tm)),
               "r"(src), "r"(0), "r"(c1), "r"(c2), "r"(c3)
               : "memory");
  asm volatile("cp.async.bulk.commit_group;\n" ::: "memory");
}
__device__ __forceinline__ constexpr uint64_t w_desc(uint32_t saddr) {
  return (uint64_t)((saddr & 0x3FFFF) >> 4) | ((uint64_t)(1024 >> 4) << 16) | ((uint64_t)(512 >> 4) << 32) | ((uint64_t)2 << 62);
}
__device__ __forceinline__ constexpr uint64_t a_desc(uint32_t saddr) {
  return (uint64_t)((saddr & 0x3FFFF) >> 4) | ((uint64_t)1 << 16) | ((uint64_t)(VROW >> 4) << 32) | ((uint64_t)2 << 62);
}
#define ACC_OPERANDS(c, d)                                                                                        \
  c(d[0]), c(d[1]), c(d[2]), c(d[3]), c(d[4]), c(d[5]), c(d[6]), c(d[7]), c(d[8]),      \
      c(d[9]), c(d[10]), c(d[11]), c(d[12]), c(d[13]), c(d[14]), c(d[15]), c(d[16]),       \
      c(d[17]), c(d[18]), c(d[19]), c(d[20]), c(d[21]), c(d[22]), c(d[23]), c(d[24]),      \
      c(d[25]), c(d[26]), c(d[27]), c(d[28]), c(d[29]), c(d[30]), c(d[31]), c(d[32]),      \
      c(d[33]), c(d[34]), c(d[35]), c(d[36]), c(d[37]), c(d[38]), c(d[39]), c(d[40]),      \
      c(d[41]), c(d[42]), c(d[43]), c(d[44]), c(d[45]), c(d[46]), c(d[47])
#define ACC_LIST                                                                   \
  "{%0, %1, %2, %3, %4, %5, %6, %7, %8, %9, %10, %11, %12, %13, %14, %15, "        \
  "%16, %17, %18, %19, %20, %21, %22, %23, %24, %25, %26, %27, %28, %29, %30, %31, " \
  "%32, %33, %34, %35, %36, %37, %38, %39, %40, %41, %42, %43, %44, %45, %46, %47}, "
__device__ __forceinline__ void wgmma_ss(float* d, uint64_t adesc, uint64_t bdesc, uint32_t accumulate) {
  asm volatile(
      "{\n.reg .pred p;\nsetp.ne.b32 p, %50, 0;\n"
      "wgmma.mma_async.sync.aligned.m64n96k16.f32.bf16.bf16 " ACC_LIST "%48, %49, p, 1, 1, 0, 1;\n}\n"
      : ACC_OPERANDS("+f", d)
      : "l"(adesc), "l"(bdesc), "r"(accumulate));
}
__device__ __forceinline__ void wgmma_def(float* d, uint64_t desc, uint32_t on) {
  asm volatile(
      "{\n.reg .pred p, q;\nsetp.ne.b32 p, 0, 0;\nsetp.ne.b32 q, %49, 0;\n"
      "@q wgmma.mma_async.sync.aligned.m64n96k16.f32.bf16.bf16 " ACC_LIST "%48, %48, p, 1, 1, 1, 1;\n}\n"
      : ACC_OPERANDS("=f", d)
      : "l"(desc), "r"(on));
}
__device__ __forceinline__ void wgmma_rs(float* d, const uint32_t* a, uint64_t bdesc, uint32_t accumulate = 1) {
  asm volatile(
      "{\n.reg .pred p;\nsetp.ne.b32 p, %53, 0;\n"
      "wgmma.mma_async.sync.aligned.m64n96k16.f32.bf16.bf16 " ACC_LIST "{%48, %49, %50, %51}, %52, p, 1, 1, 1;\n}\n"
      : ACC_OPERANDS("+f", d)
      : "r"(a[0]), "r"(a[1]), "r"(a[2]), "r"(a[3]), "l"(bdesc), "r"(accumulate));
}
__device__ __forceinline__ void wgmma_fence() { asm volatile("wgmma.fence.sync.aligned;\n" ::: "memory"); }
__device__ __forceinline__ void wgmma_commit() { asm volatile("wgmma.commit_group.sync.aligned;\n" ::: "memory"); }
template <int N>
__device__ __forceinline__ void wgmma_wait() { asm volatile("wgmma.wait_group.sync.aligned %0;\n" ::"n"(N) : "memory"); }
__device__ __forceinline__ void acc_fence(float* d) {
#pragma unroll
  for (int i = 0; i < 48; i++) asm volatile("" : "+f"(d[i])::"memory");
}
#define UPD(text, d, e, c) asm volatile("{\n.reg .pred p;\nsetp.eq.u32 p, %3, 0;\n@p " text ";\n}\n" : "+f"(d) : "f"(e), "f"(c), "r"(guard))
#define UPD_ADD(d, e, c) UPD("fma.rn.f32 %0, %1, %2, %0", d, e, c)
#define UPD_MUL(d, e, c) UPD("fma.rn.f32 %0, %0, %2, %1", d, e, c)
__device__ __forceinline__ void keep_alive8(const uint32_t* a, uint32_t never) {
  asm volatile(
      "{\n.reg .pred p, q;\nsetp.eq.u32 p, %8, 16;\nsetp.eq.u32 q, %8, 32;\n"
      "@p st.shared.v4.b32 [%8], {%0, %1, %2, %3};\n@q st.shared.v4.b32 [%8], {%4, %5, %6, %7};\n}\n" ::"r"(a[0]),
      "r"(a[1]), "r"(a[2]), "r"(a[3]), "r"(a[4]), "r"(a[5]), "r"(a[6]), "r"(a[7]), "r"(never)
      : "memory");
}
__device__ __forceinline__ void keep_alive4(const uint32_t* a, uint32_t never) {
  asm volatile("{\n.reg .pred p;\nsetp.eq.u32 p, %4, 16;\n@p st.shared.v4.b32 [%4], {%0, %1, %2, %3};\n}\n" ::"r"(a[0]), "r"(a[1]), "r"(a[2]),
               "r"(a[3]), "r"(never) : "memory");
}
__device__ __forceinline__ void ldsm4(uint32_t& r0, uint32_t& r1, uint32_t& r2, uint32_t& r3, uint32_t addr) {
  asm volatile("ldmatrix.sync.aligned.m8n8.x4.shared.b16 {%0, %1, %2, %3}, [%4];\n"
               : "=r"(r0), "=r"(r1), "=r"(r2), "=r"(r3)
               : "r"(addr)
               : "memory");
}
__device__ __forceinline__ void ldsm4(uint32_t* r, uint32_t addr) { ldsm4(r[0], r[1], r[2], r[3], addr); }
__device__ __forceinline__ void stsm4(uint32_t addr, const uint32_t* r) {
  asm volatile("stmatrix.sync.aligned.m8n8.x4.shared.b16 [%0], {%1, %2, %3, %4};\n" ::"r"(addr), "r"(r[0]), "r"(r[1]), "r"(r[2]), "r"(r[3])
               : "memory");
}
__device__ __forceinline__ void arrive_if(uint32_t bar) {
  asm volatile("{\n.reg .pred p;\nsetp.ne.u32 p, %0, 0;\n@p mbarrier.arrive.shared::cluster.b64 _, [%0];\n}\n" ::"r"(bar) : "memory");
}
__device__ __forceinline__ uint32_t lds32(uint32_t addr) {
  uint32_t v;
  asm volatile("ld.shared.u32 %0, [%1];\n" : "=r"(v) : "r"(addr) : "memory");
  return v;
}
__device__ __forceinline__ void lds64(uint32_t& a, uint32_t& b, uint32_t addr) {
  asm volatile("ld.shared.v2.u32 {%0, %1}, [%2];\n" : "=r"(a), "=r"(b) : "r"(addr) : "memory");
}
__device__ __forceinline__ void lds128(uint32_t* v, uint32_t addr) {
  asm volatile("ld.shared.v4.b32 {%0, %1, %2, %3}, [%4];\n" : "=r"(v[0]), "=r"(v[1]), "=r"(v[2]), "=r"(v[3]) : "r"(addr) : "memory");
}
__device__ __forceinline__ void sts128(uint32_t addr, const uint32_t* v) {
  asm volatile("st.shared.v4.b32 [%0], {%1, %2, %3, %4};\n" ::"r"(addr), "r"(v[0]), "r"(v[1]), "r"(v[2]), "r"(v[3]) : "memory");
}
__device__ __forceinline__ void sts64(uint32_t addr, const uint32_t* v) {
  asm volatile("st.shared.v2.b32 [%0], {%1, %2};\n" ::"r"(addr), "r"(v[0]), "r"(v[1]) : "memory");
}
__device__ __forceinline__ void sts32(uint32_t addr, uint32_t v) {
  asm volatile("st.shared.u32 [%0], %1;\n" ::"r"(addr), "r"(v) : "memory");
}
__device__ __forceinline__ void fence_async() { asm volatile("fence.proxy.async.shared::cta;\n" ::: "memory"); }
__device__ __forceinline__ void bar_sync(int id, int n) { asm volatile("bar.sync %0, %1;\n" ::"r"(id), "r"(n) : "memory"); }
__device__ __forceinline__ __nv_bfloat162 as_bf2(uint32_t v) { return *reinterpret_cast<__nv_bfloat162*>(&v); }
__device__ __forceinline__ uint32_t as_u32(__nv_bfloat162 v) { return *reinterpret_cast<uint32_t*>(&v); }
__device__ __forceinline__ uint32_t hfma2(uint32_t c, uint32_t a, uint32_t b) { return as_u32(__hfma2(as_bf2(c), as_bf2(a), as_bf2(b))); }
__device__ __forceinline__ uint32_t hadd2(uint32_t a, uint32_t b) { return as_u32(__hadd2(as_bf2(a), as_bf2(b))); }
__device__ __forceinline__ uint32_t hsub2(uint32_t a, uint32_t b) { return as_u32(__hsub2(as_bf2(a), as_bf2(b))); }
__device__ __forceinline__ __nv_bfloat162 half_of(uint32_t w, int hi) { return hi ? __high2bfloat162(as_bf2(w)) : __low2bfloat162(as_bf2(w)); }
__device__ __forceinline__ uint32_t hmul2_h(uint32_t w, int hi, uint32_t a) { return as_u32(__hmul2(half_of(w, hi), as_bf2(a))); }
__device__ __forceinline__ uint32_t hfma2_h(uint32_t w, int hi, uint32_t a, uint32_t c) {
  return as_u32(__hfma2(half_of(w, hi), as_bf2(a), as_bf2(c)));
}
__device__ __forceinline__ uint32_t pack2(float lo, float hi) { return as_u32(__floats2bfloat162_rn(lo, hi)); }
__device__ __forceinline__ uint32_t prmt(uint32_t a, uint32_t b, uint32_t sel) {
  uint32_t r;
  asm("prmt.b32 %0, %1, %2, %3;\n" : "=r"(r) : "r"(a), "r"(b), "r"(sel));
  return r;
}
__device__ __forceinline__ uint32_t absmax2(uint32_t a, uint32_t b) {
  uint32_t r;
  asm("max.NaN.xorsign.abs.bf16x2 %0, %1, %2;\n" : "=r"(r) : "r"(a), "r"(b));
  return r;
}
__device__ __forceinline__ uint32_t clip2(uint32_t p) {
  return as_u32(__hmin2(__hmax2(as_bf2(p), as_bf2(0u)), as_bf2(0x435f435fu)));
}
__device__ __forceinline__ constexpr uint32_t tap_delta(int a, int b) {
  return (a == 0 ? 0xbf80u : a == 1 ? 0u : 0x3f80u) | (b == 0 ? 0xbf800000u : b == 1 ? 0u : 0x3f800000u);
}
__device__ __forceinline__ void coefs(uint32_t w, uint32_t& p0, uint32_t& p1) {
  const uint32_t o = hsub2(0x3f803f80u, w);
  const uint32_t xa = __byte_perm(o, w, 0x7632);
  p0 = hmul2_h(o, 0, xa);
  p1 = hmul2_h(w, 0, xa);
}
__device__ __forceinline__ uint32_t frac2(uint32_t pos) {
  const float py = bf16lo(pos), px = bf16hi(pos);
  return __byte_perm(__float_as_uint(py - floorf(py)), __float_as_uint(px - floorf(px)), 0x7632);
}
__device__ __forceinline__ void blend4(uint32_t* t, const uint32_t* g, const uint32_t* h, const uint32_t* k, uint32_t a0,
                                       uint32_t a1, uint32_t b0, uint32_t b1) {
#pragma unroll
  for (int i = 0; i < 4; i++) {
    const uint32_t p0 = (i & 1) ? b0 : a0, p1 = (i & 1) ? b1 : a1;
    t[i] = hfma2_h(p1, 1, k[i], hfma2_h(p1, 0, h[i], hfma2_h(p0, 1, g[i], hmul2_h(p0, 0, t[i]))));
  }
}
__device__ __forceinline__ bool elect_one() {
  uint32_t r;
  asm volatile("{\n.reg .pred p;\nelect.sync _|p, 0xffffffff;\nselp.u32 %0, 1, 0, p;\n}\n" : "=r"(r));
  return r != 0;
}

template <int N>
__device__ __forceinline__ void transform6(const uint32_t (*a)[N], const uint32_t (*b)[N], const uint32_t (*c)[N], uint32_t dst, uint32_t off0) {
  const uint32_t* d[6] = {a[0], a[1], b[0], b[1], c[0], c[1]};
  uint32_t v[N], t[N], u[N];
  auto put = [&](int slot, const uint32_t* r) {
    const uint32_t p = slot < 4 ? dst + slot * VSLOT : dst + off0 + (slot - 4) * VSLOT;
    if (N == 4) sts128(p, r);
    else sts64(p, r);
  };
#pragma unroll
  for (int k = 0; k < 2; k++) {
#pragma unroll
    for (int i = 0; i < N; i++) v[i] = hfma2(0xc088c088u, d[2 + k][i], hadd2(d[k][i], d[4 + k][i]));
    put(4 + k, v);
  }
#pragma unroll
  for (int k = 0; k < 2; k++) {
    const uint32_t q = k ? 0xbe80be80u : 0xc080c080u, f = k ? 0x40004000u : 0x3f003f00u;
#pragma unroll
    for (int i = 0; i < N; i++) {
      t[i] = hfma2(q, d[2][i], d[4][i]);
      u[i] = hfma2(q, d[1][i], d[3][i]);
      v[i] = hfma2(f, u[i], t[i]);
    }
    put(2 * k, v);
#pragma unroll
    for (int i = 0; i < N; i++) t[i] = hfma2(f ^ 0x80008000u, u[i], t[i]);
    put(2 * k + 1, t);
  }
}

template <bool FP32>
__device__ __forceinline__ void weights4(const uint32_t* g0, const uint32_t* g1, const uint32_t* g2, uint32_t (*u)[4]) {
#pragma unroll
  for (int i = 0; i < 4; i++) {
    if (FP32) {
      float r[4][2];
#pragma unroll
      for (int h = 0; h < 2; h++) {
        const float a = h ? bf16hi(g0[i]) : bf16lo(g0[i]), b = h ? bf16hi(g1[i]) : bf16lo(g1[i]), c = h ? bf16hi(g2[i]) : bf16lo(g2[i]);
        const float ea = fmaf(0.25f, c, a) * -0.5f, eb = fmaf(0.25f, a, c);
        r[0][h] = fmaf(-0.25f, b, ea);
        r[1][h] = fmaf(0.25f, b, ea);
        r[2][h] = fmaf(0.5f, b, eb);
        r[3][h] = fmaf(-0.5f, b, eb);
      }
#pragma unroll
      for (int k = 0; k < 4; k++) u[k][i] = pack2(r[k][0], r[k][1]);
    } else {
      const uint32_t ea = hfma2(0xbe00be00u, g2[i], as_u32(__hmul2(as_bf2(g0[i]), as_bf2(0xbf00bf00u))));
      u[0][i] = hfma2(0xbe80be80u, g1[i], ea);
      u[1][i] = hfma2(0x3e803e80u, g1[i], ea);
      const uint32_t eb = hfma2(0x3e803e80u, g0[i], g2[i]);
      u[2][i] = hfma2(0x3f003f00u, g1[i], eb);
      u[3][i] = hfma2(0xbf00bf00u, g1[i], eb);
    }
  }
}

template <int GROUP = 4096>
__device__ __forceinline__ void stage_slab(const float* acc, uint32_t stg, int lane) {
  const uint32_t a = stg + (lane & 15) * 64 + (((lane >> 4) ^ ((lane >> 1) & 3)) << 4);
#pragma unroll
  for (int jp = 0; jp < 6; jp++) {
    uint32_t pk[4];
#pragma unroll
    for (int i = 0; i < 4; i++) pk[i] = pack2(acc[jp * 8 + i * 2], acc[jp * 8 + i * 2 + 1]);
    stsm4((a ^ ((jp & 1) * 32)) + (jp >> 1) * GROUP, pk);
  }
}
__device__ __forceinline__ void publish(uint32_t bar, int lane) {
  fence_async();
  __syncwarp();
  arrive_if(lane == 0 ? bar : 0u);
}
__device__ __forceinline__ constexpr uint32_t w_slot(int st) {
  return st < 3 ? SM_WW + st * STAGE : st == 3 ? 12 * VSLOT : st < 11 ? SM_WW + (st - 4) % 3 * STAGE : st < 13 ? 4 * VSLOT + (st - 11) * STAGE
         : st < 16 ? SM_WW + st % 3 * STAGE : st == 16 ? 4 * VSLOT : STAGE;
}
__device__ __forceinline__ constexpr uint64_t w_slots(int st0, int step, int n) {
  uint64_t r = 0;
  for (int i = 0; i < n; i++) r |= (uint64_t)(w_slot(st0 + i * step) >> 10) << (8 * i);
  return r;
}
__device__ __forceinline__ uint32_t w_stg(int wg, int i) {
  return wg ? (i == 2 ? 0 : i == 1 ? SM_R + 24576 : i == 0 ? 4 * VSLOT + STAGE : SM_WW + STAGE) : SM_R + (i == 2 ? 24576 : (i & 1) * 12288);
}

__device__ __forceinline__ void ldsm4_if(uint32_t* r, uint32_t addr, uint32_t on) {
  asm volatile(
      "{\n.reg .pred p;\nsetp.ne.u32 p, %5, 0;\n"
      "@p ldmatrix.sync.aligned.m8n8.x4.shared.b16 {%0, %1, %2, %3}, [%4];\n}\n"
      : "+r"(r[0]), "+r"(r[1]), "+r"(r[2]), "+r"(r[3])
      : "r"(addr), "r"(on)
      : "memory");
}
__device__ __forceinline__ void push_record(uint32_t bars, uint32_t key, uint32_t pos) {
  uint32_t slot;
  asm volatile("atom.shared.add.u32 %0, [%1], 1;\n" : "=r"(slot) : "r"(bars + O_CNT) : "memory");
  const uint32_t v[2] = {key, pos};
  if (slot < NREC) sts64(bars + O_REC + slot * 8, v);
}
__device__ __forceinline__ void put_sel(uint32_t bars, uint32_t key, int lane) {
  if (lane < NREC)
    asm volatile("st.shared.u16 [%0], %1;\n" ::"r"(bars + O_SEL + (lane & 6) * 4 + (lane >> 3) * 4 + (lane & 1) * 2), "h"((uint16_t)((key >> 20) | 0x4000u)) : "memory");
}
__device__ __noinline__ void push_taps(uint32_t bars, uint32_t key, uint32_t taps, const uint32_t* __restrict__ offs) {
  const int y = key & 255, x = (key >> 8) & 255;
#pragma unroll 1
  for (; taps; taps &= taps - 1) {
    const int tap = __ffs(taps) - 1, ki = (tap * 11) >> 5;
    const uint32_t gp = pack2((float)(y + ki - 1), (float)(x + tap - ki * 3 - 1));
    push_record(bars, key | (tap << 16), clip2(hadd2(gp, __ldg(offs + (y * IW + x) * 9 + tap))));
  }
}
__device__ __forceinline__ uint32_t wino_key(int y, int x) {
  return y | (x << 8) | ((((y & 28) << 1) | (x & 7)) << 20) | ((((x & 8) >> 1) | (y & 3)) << 27);
}
__device__ __forceinline__ uint32_t strip_key(int u, int v, int left) {
  return (left ? v | (u << 8) : u | (v << 8)) | ((((u & 15) << 3) | (v & 7)) << 20) | ((u >> 4) << 29);
}
__device__ __forceinline__ bool strip_off(uint32_t d, bool out) { return (d & 0x7fff) || (d & 0x7fff7fffu) > (out ? 0u : 0x3f000000u); }
__device__ __forceinline__ void delta(uint32_t* v, uint32_t key, uint32_t pos, const uint4* __restrict__ x, int c) {
  const int tap = (key >> 16) & 15, ki = (tap * 11) >> 5, gy = (int)bf16lo(pos), gx = (int)bf16hi(pos);
  const int cy = min(max((int)(key & 255) + ki - 1, 0), IH - 1), cx = min(max((int)((key >> 8) & 255) + tap - ki * 3 - 1, 0), IW - 1);
  const uint32_t sx = gx < IW - 1 ? 12 : 0, sy = gy < IH - 1 ? IW * 12 : 0, p = (gy * IW + gx) * 12 + c;
  uint4 t[5] = {__ldg(x + p), __ldg(x + (p + sx)), __ldg(x + (p + sy)), __ldg(x + (p + sy + sx)), __ldg(x + (uint32_t)((cy * IW + cx) * 12 + c))};
  uint32_t q0, q1;
  coefs(frac2(pos), q0, q1);
  blend4(&t[0].x, &t[1].x, &t[2].x, &t[3].x, q0, q1, q0, q1);
#pragma unroll
  for (int i = 0; i < 4; i++) v[i] = hsub2((&t[0].x)[i], (&t[4].x)[i]);
}
__device__ __forceinline__ void fixup(uint32_t bars, int w, int n, const uint4* __restrict__ x, const uint4* __restrict__ wgt) {
  const uint32_t fix = bars + SM_FIX - SM_BAR + 3072, part = fix + 3072;
  const int lane = lane_now(), l = min(lane, 23), up = l >= 12;
#pragma unroll 1
  for (int r = 0; r < n; r++) {
    uint32_t key, pos, sum[4];
    lds64(key, pos, bars + O_REC + r * 8);
    key = __shfl_sync(0xffffffffu, key, 0);
    pos = __shfl_sync(0xffffffffu, pos, 0);
    delta(sum, key, pos, x, w * 3 + (l >> 3));
    sts128(part + w * 192 + (l >> 3) * 16, sum);
    __syncwarp();
#pragma unroll
    for (int i = 0; i < 4; i++) sum[i] = 0;
    const uint4* wp = wgt + (uint32_t)((((key >> 16) & 15) * 96 + w * 24 + up * 11) * 12 + l);
#pragma unroll 1
    for (int h = 0; h < 2; h++) {
      uint4 wv[6];
#pragma unroll
      for (int k = 0; k < 6; k++) wv[k] = __ldg(wp + (h * 6 + k) * 12);
#pragma unroll
      for (int k = 0; k < 3; k++) {
        const uint32_t d = lds32(part + w * 192 + up * 24 + h * 12 + k * 4);
#pragma unroll
        for (int i = 0; i < 4; i++) sum[i] = hadd2(sum[i], hfma2_h(d, 1, (&wv[2 * k + 1].x)[i], hmul2_h(d, 0, (&wv[2 * k].x)[i])));
      }
    }
#pragma unroll
    for (int i = 0; i < 4; i++) sum[i] = hadd2(sum[i], __shfl_down_sync(0xffffffffu, sum[i], 12));
    if (lane < 12) sts128(part + w * 192 + lane * 16, sum);
    bar_sync(4, 128);
    if (lane < 12) {
      float lo = 0.0f, hi = 0.0f;
#pragma unroll
      for (int k = 0; k < 4; k++) {
        const uint32_t v = lds32(part + k * 192 + w * 48 + lane * 4);
        lo += bf16lo(v);
        hi += bf16hi(v);
      }
      sts32(fix + r * 192 + w * 48 + lane * 4, pack2(lo, hi));
    }
    bar_sync(4, 128);
  }
}
__device__ __forceinline__ void select_rows(uint32_t* A, const uint32_t* sel, uint32_t code, bool scale) {
#pragma unroll
  for (int i = 0; i < 4; i++) {
    A[i] = as_u32(__heq2(as_bf2(sel[i >> 1]), as_bf2(code + (i & 1) * 0x80008u)));
    if (scale) A[i] = as_u32(__hmul2(as_bf2(A[i]), as_bf2(0x3ff03ff0u)));
  }
}
struct Maps {
  CUtensorMap x[5];
  CUtensorMap w[2];
  CUtensorMap o[2];
  CUtensorMap out[4];
};

__global__ void __cluster_dims__(2, 1, 1) __launch_bounds__(NTHREADS, 1)
dcn_kernel(const __nv_bfloat16* __restrict__ x, const uint32_t* __restrict__ offs, const uint4* __restrict__ wgt, Scratch* scr,
           const uint32_t never, const __grid_constant__ Maps tm) {
  extern __shared__ __align__(1024) uint8_t smem[];
  const uint32_t sbase = smem_u32(smem);
  const uint32_t bars = sbase + SM_BAR;
  const uint32_t tstart = clock32();
  const int tid = threadIdx.x;
  const int cta = blockIdx.x - NC;
  const int wid = __shfl_sync(0xffffffffu, tid >> 5, 0);
  const int lane = tid & 31;
  const bool wino = (uint32_t)cta < NW, strip = cta >= NW;
  const int left = (uint32_t)cta >= NW + NG / 2;
  const int ry = (cta * 43) >> 9;
  const int x0 = wino ? 32 + (cta - ry * 12) * 16 : 32 + (cta - NW - left * (NG / 2)) * 8, y0 = 32 + ry * 32;
  auto load_cols = [&](int s, int j) {
    const uint32_t dst = sbase + (s ? SM_R : 4 * VSLOT) + j * 2 * PIECE, bar = bars + (B_XF + s * 5 + j) * 8;
    if (j < 4) tma_load_x4(dst, &tm.x[4], bar, s * 32, y0 - 1, (x0 >> 1) - 1 + j * 2);
    else tma_load_x(dst, &tm.x[0], bar, 0, s * 32, x0 + 15, y0 - 1);
  };
  auto corner_tile = [&](int wg) {
    const uint32_t t = ((wg ? 0xfeba00000000ull : 0xd976c8325410ull) >> (4 * (cta + NC))) & 15;
    return (t & 3) | ((t >> 2) << 8);
  };
  auto load_cx = [&](int wg, int g, uint32_t tl) {
    tma_load_x(sbase + SM_CX + wg * CWIN + g * CSLICE, &tm.x[3], bars + (B_XF + wg * 3 + g) * 8, CSLICE, g * 32, (int)(tl & 255) * 8 - 2,
               (int)(tl >> 8) * 8 - 2);
  };
  const bool one = elect_one();
  if (wid == 0 && one) {
    asm volatile("prefetch.tensormap [%0];\n" ::"l"(reinterpret_cast<uint64_t>(wino ? &tm.x[4] : &tm.o[1])) : "memory");
    asm volatile("prefetch.tensormap [%0];\n" ::"l"(reinterpret_cast<uint64_t>(&tm.x[0])) : "memory");
  }
  if (wid == 15) {
    if (one) {
      if (wino) {
        mbar_init(bars + B_W2 * 8, 1);
#pragma unroll
        for (int k = 0; k < 9; k++)
          asm volatile("cp.async.bulk.shared::cluster.global.mbarrier::complete_tx::bytes [%0], [%1], 6144, [%2];\n" ::"r"(sbase + k * 6144 + (k < 6 ? 0 : 6 * VSLOT)),
                       "l"(wgt + k * 1152), "r"(bars + B_W2 * 8) : "memory");
      }
#pragma unroll
      for (int j = 0; j < 8; j++) mbar_init(bars + j * 8, 1);
      if (wino) {
#pragma unroll
        for (int j = 0; j < 5; j++) load_cols(0, j);
        mbar_expect_tx(bars + B_W2 * 8, 9 * 6144);
      } else {
        mbar_expect_tx(bars + B_OG * 8, strip ? 4 * 2304 : 2 * 2304);
#pragma unroll
        for (int k = 0; k < 4; k++) {
          const uint32_t tl = corner_tile(k & 1);
          if (strip || k < 2)
            tma_load_o(sbase + (strip ? SM_GO + k * 2304 : SM_CX + k * CWIN + 2 * CSLICE), &tm.o[1], bars + B_OG * 8,
                       strip ? (left ? k * 8 : x0) : (tl & 255) * 8, strip ? (left ? x0 : k * 8) : (tl >> 8) * 8);
        }
        if (strip) {
          asm volatile("prefetch.tensormap [%0];\n" ::"l"(reinterpret_cast<uint64_t>(&tm.x[1 + left])) : "memory");
        } else {
          load_cx(0, 0, corner_tile(0));
          if (cta >= -4) load_cx(1, 0, corner_tile(1));
        }
        asm volatile("prefetch.tensormap [%0];\n" ::"l"(reinterpret_cast<uint64_t>(&tm.w[left])) : "memory");
      }
      asm volatile("fence.mbarrier_init.release.cluster;\n" ::: "memory");
    }
    __syncwarp();
  }
  const bool prep = wid >= 8 && wid < 11 && strip && cta < NW + 24;
  uint4 g[3];
  if (prep) {
    const uint4* src = wgt + (uint32_t)((cta - NW + ((cta - NW) >> 3) * 4) * 96 + 352 + (tid >> 5) * 4 + (lane >> 2) * 12 + (lane & 3));
#pragma unroll
    for (int k = 0; k < 3; k++) g[k] = __ldg(src + k * 3456);
  }
  if (wid < 8 || wid >= 12) {
    if (one && wid < 15) {
      const int grp = wid < 8 ? 4 + wid : 15 - wid;
#pragma unroll
      for (int i = 0; i < 8; i++) mbar_init(bars + grp * 64 + i * 8, grp < 5 ? 1 : grp < 7 ? 16 : grp < 8 ? 8 : 4);
      asm volatile("fence.mbarrier_init.release.cluster;\n" ::: "memory");
    }
    __syncwarp();
  } else if (one && wid == 11) {
    const uint32_t z[2] = {0, 1u << 31};
    sts64(bars + O_CNT, z);
    __threadfence_block();
  }
  asm volatile("barrier.cluster.arrive.relaxed.aligned;\n" ::: "memory");
  auto load_cw = [&](int st) {
    const uint32_t rank = cta & 1;
    const int g = (st * 11) >> 5;
    const uint32_t fb = bars + (B_WF + st) * 8;
    mbar_expect_tx(fb, STAGE);
    tma_load_w(sbase + st * STAGE, &tm.w[1], fb, g * 32, 0, st - g * 3, 1u << rank);
    tma_load_w(sbase + st * STAGE + STAGE / 2, &tm.w[1], fb, g * 32 + 16, 0, st - g * 3, 1u << rank);
  };
  if (wid < 8) {
    const int wg = wid >> 2, warp = wid & 3, lane = lane_now();
    if ((sbase & 0xffffff) != SB) __trap();
    const int src = cta + NC, t = tid & 127;
    const int lf = src == 0 || src == 7 ? t < 64 : src >= 4;
    const int along = ((0x0c84b842u >> (4 * src)) & 15) * 16 + (src == 0 || src == 7 ? (t >> 1) & 31 : t >> 1);
    const int oy = lf ? along : 32 + (t & 1), ox = lf ? 32 + (t & 1) : along;
    const bool own = src == 0 ? !lf || along >= 34 : along < (src == 2 ? 176 : 224);
    uint32_t o2[9], tag;
    if (src < 8 && wg) {
      tag = scr->launch[blockIdx.x] + 1;
#pragma unroll
      for (int m = 0; m < 9; m++) o2[m] = __ldg(offs + (min(oy, IH - 1) * IW + min(ox, IW - 1)) * 9 + m);
    }
    asm volatile("setmaxnreg.inc.sync.aligned.u32 224;\n");
    asm volatile("barrier.cluster.wait.acquire.aligned;\n" ::: "memory");
    uint32_t we_addr;
    asm volatile("mapa.shared::cluster.u32 %0, %1, %2;\n" : "=r"(we_addr) : "r"(bars + B_WE * 8), "r"(lane & 1));
    const uint32_t nv = never & (uint32_t)tid;
    float acc[4][48];
    int ntiles = 0;
    uint32_t tile0 = 0, tstep = 0;
    if (wino) {
      {
        const uint32_t dst = sbase + (wid & 2) * (STAGE / 4) + (wid & 1) * 512 + (lane >> 2) * 64 + (((lane ^ (lane >> 3)) & 3) << 4);
        const uint32_t src = sbase + warp * 1536 + (lane >> 2) * 192 + (lane & 3) * 16;
        mbar_wait(bars + B_W2 * 8);
        uint32_t gg[3][4], u[4][4];
        auto get = [&](int n) {
          const uint32_t a = src + n * 64 + ((n * 11) >> 5) * (6144 - 192);
          lds128(gg[0], a);
          lds128(gg[2], a + 10 * VSLOT);
          lds128(gg[1], a + 18432);
        };
        get(wg);
#pragma unroll 1
        for (int n = wg; n < 9; n += 2) {
          weights4<false>(gg[0], gg[1], gg[2], u);
          if (n < 7) get(n + 2);
#pragma unroll
          for (int k = 0; k < 4; k++) sts128(dst + n * 1024 + w_slot(k), u[k]);
        }
        fence_async();
        bar_sync(12, 384);
      }
      {
        const int q = wid + wg, tp = lane >> 3, h = tp * 18 + q;
        const uint32_t src = (sbase + 4 * VSLOT + q * PIECE + tp * 1024 + (lane & 7) * 16) & (x0 + 2 * q == IW ? ~64u : ~0u);
        const uint32_t vb = sbase + h * 128 + (lane & 4) * 16;
        mbar_wait(bars + (B_XF + (q >> 1)) * 8);
        uint32_t d[10][4];
#pragma unroll
        for (int r = 0; r < 9; r++) lds128(d[r], src + r * 128);
        lds128(d[9], src + (y0 + 32 == IH && tp == 3 ? 8 * 128 : 9 * 128));
        transform6<4>(d, d + 2, d + 4, vb + (((lane ^ h) & 3) << 4), 10 * VSLOT);
        transform6<4>(d + 4, d + 6, d + 8, vb + VROW + (((lane ^ (h + 1)) & 3) << 4), 10 * VSLOT);
        publish(bars + (wg ? B_VF + 1 : B_V0) * 8, lane);
      }
      constexpr uint64_t bd0 = w_desc(SB);
      const uint64_t ad0 = a_desc(SB) + wg * 32;
      uint32_t rel = 0;
      if (lane == 3) we_addr = bars + (B_VE - 3) * 8;
      if (lane == 2) we_addr = bars + (B_WL - 13) * 8;
      uint32_t guard = never, gnext = never;
#define PIN_NEXT do { guard = gnext; gnext = clock32() & never; } while (0)
      auto stage = [&](float* a, int st, uint32_t rs, int vslot, uint32_t accumulate, auto work, bool retire = true, bool await = true) {
        const uint64_t bd = bd0 + (rs >> 4), ad = ad0 + vslot * (VSLOT >> 4);
        if (await) mbar_wait(bars + (B_WF + st) * 8);
        wgmma_fence();
#pragma unroll
        for (int j = 0; j < 6; j++) {
          wgmma_ss(a, ad + (j >> 1) * 4 + (j & 1) * 2, bd + (j >> 1) * WTAP + (j & 1) * WHALF, j ? 1 : accumulate);
          if (j == 1 && retire) {
            wgmma_commit();
            wgmma_wait<1>();
            arrive_if(rel);
            rel = ((lane < 2 ? 0xff7u : lane == 3 ? 8u : lane == 2 ? 0x2000u : 0u) >> st) & 1 ? we_addr + st * 8 : 0u;
          }
          if (j == 5) wgmma_commit();
          work(j);
        }
      };
#pragma unroll
      for (int p = 0; p < 4; p++) {
        wgmma_fence();
        wgmma_def(acc[p], w_desc(SB + SM_WW), never);
      }
      wgmma_commit();
      mbar_wait(bars + B_V0 * 8);
      if (wg) mbar_wait(bars + (B_VF + 1) * 8);
#pragma unroll 1
      for (int s = 0; s < 3; s++) {
        if (s) {
          const uint32_t vf = bars + (wg ? B_VB + s : B_VF + 2 * s) * 8;
          if (wg || !__all_sync(0xffffffffu, mbar_poll(vf))) {
            wgmma_wait<0>();
            arrive_if(rel);
            rel = 0;
            if (wg) {
              const int ty = warp * 2 + (lane >> 4);
              const uint32_t src = sbase + SM_R + 8 * PIECE + ty * 512 + (lane & (x0 + 16 == IW ? 7 : 15)) * 8;
              mbar_wait(bars + (B_XF + s * 5 + 4) * 8);
              uint32_t d[6][2];
#pragma unroll
              for (int r = 0; r < 5; r++) lds64(d[r][0], d[r][1], src + r * 128);
              lds64(d[5][0], d[5][1], src + (y0 + 4 * ty + 4 == IH ? 4 * 128 : 5 * 128));
              transform6<2>(d, d + 2, d + 4, sbase + (s & 1) * 4 * VSLOT + ty * VROW + 1024 + (lane & 8) * 8 + (lane & 1) * 8 + ((((lane >> 1) ^ ty) & 3) << 4),
                            s & 1 ? 4 * VSLOT : 12 * VSLOT);
              fence_async();
              __syncwarp();
              arrive_if(lane == 0 ? vf : lane == 1 && s == 1 ? bars + (B_RE + 4) * 8 : 0u);
            }
            mbar_wait(vf);
            if (wg && s == 2) mbar_wait(bars + B_PP * 8);
          }
        }
#pragma unroll
        for (int p = 0; p < 4; p++) {
          stage(acc[p], s * 4 + p, (((uint32_t)w_slots(p, 4, 3) >> (8 * s)) & 255) << 10, (s & 1) * 4 + p, s, [&](int j) {
            if (p == 2 && j == 3) arrive_if(lane == 0 && !wg && s == 2 ? bars + B_PP * 8 : 0u);
          });
        }
      }
      mbar_wait(bars + (B_WF + 12) * 8);
      uint32_t imp = lds32(bars + O_CNT + 4);
#pragma unroll
      for (int i = 0; i < 48; i++) {
        if (i % 8 == 0) PIN_NEXT;
        UPD_ADD(acc[0][i], acc[1][i], 1.0f);
        UPD_MUL(acc[1][i], acc[0][i], -2.0f);
      }
      wgmma_wait<0>();
      arrive_if(rel);
      rel = 0;
      imp = __ballot_sync(0xffffffffu, (imp >> lane) & 1);
      uint32_t sel[2], A[4];
      if ((imp >> (wg * 4)) & ~0xf0f0u) {
        mbar_wait(bars + B_IM * 8);
        if ((int)imp < 0) imp = __ballot_sync(0xffffffffu, (lds32(bars + O_CNT + 4) >> lane) & 1);
        lds64(sel[0], sel[1], bars + O_SEL + (lane & 3) * 8);
      }
      const uint32_t code = (wg * 512 + warp * 16 + (lane >> 2) + 0x4000u) * 0x10001u;
      auto corr = [&](int p) {
#pragma unroll
        for (int i = 0; i < 4; i++) asm volatile("mov.b32 %0, 0;\n" : "=r"(A[i]));
        if ((imp >> (wg * 4 + p)) & 1) {
          select_rows(A, sel, code + p * 0x800080u, p == 1 || p == 2);
          wgmma_fence();
          wgmma_rs(acc[p], A, w_desc(SB + SM_FIX));
          wgmma_commit();
        }
      };
      auto done = [&] {
        wgmma_wait<0>();
        keep_alive4(A, nv);
      };
      auto odd = [&](int i0, int i1) {
#pragma unroll
        for (int i = 0; i < 48; i++) {
          if (i < i0 || i >= i1) continue;
          if (i % 16 == 0) PIN_NEXT;
          UPD_ADD(acc[1][i], acc[3][i], 0.5f);
          UPD_ADD(acc[3][i], acc[1][i], 2.0f / 15.0f);
        }
      };
#pragma unroll
      for (int i = 0; i < 48; i++) {
        if (i % 8 == 0) PIN_NEXT;
        if (i == 24 && !wg) mbar_wait(bars + (B_VB + 2) * 8);
        UPD_ADD(acc[2][i], acc[3][i], 1.0f);
        UPD_MUL(acc[3][i], acc[2][i], -2.0f);
        UPD_ADD(acc[2][i], acc[0][i], 0.5f);
        UPD_ADD(acc[0][i], acc[2][i], 2.0f / 15.0f);
      }
      const uint32_t stg = sbase + warp * 1024, stb = bars + (B_ST + wg * 4) * 8;
      const uint32_t sa = stg + (lane & 15) * 64 + (((lane >> 4) ^ ((lane >> 1) & 3)) << 4);
      uint32_t pk[24];
      auto put = [&](int i, int jp) { stsm4(((sa + guard + w_stg(wg, i)) ^ ((jp & 1) * 32)) + (jp >> 1) * 4096, pk + jp * 4); };
      auto row = [&](int i, int g0, int g1) {
#pragma unroll
        for (int k = g0 * 4; k < g1 * 4; k++) pk[k] = pack2(acc[i][k * 2] * (8.0f / 15.0f), acc[i][k * 2 + 1] * (8.0f / 15.0f));
        PIN_NEXT;
#pragma unroll
        for (int g = g0; g < g1; g++) put(i, g);
      };
      corr(2);
      odd(0, 16);
      done();
      acc_fence(acc[2]);
      row(2, 0, 6);
      corr(0);
      odd(16, 48);
      publish(stb + 16, lane);
      done();
      corr(1);
      auto row1 = [&](int n) {
        if (n == 1) {
          keep_alive4(A, nv);
          acc_fence(acc[1]);
        }
        if (n == 2) mbar_wait(bars + (wg ? B_SR : B_RD) * 8);
        if (n >= 2 && n < 8) row(1, n - 2, n - 1);
        if (n == 9) publish(stb + 8, lane);
      };
      stage(acc[0], 12, w_slot(12), 10, 1, [&](int j) { row1(j); }, true, false);
      stage(acc[0], 13, w_slot(13), 8, 1, [&](int j) { row1(6 + j); });
      stage(acc[0], 14, w_slot(14), 12, 1, [](int) {});
      corr(3);
      guard |= gnext;
      auto row0 = [&](int n) {
        if (n == 2) {
          if (wg) mbar_wait(bars + B_WL * 8);
          acc_fence(acc[0]);
#pragma unroll
          for (int i = 0; i < 24; i++) pk[i] = pack2(acc[0][i * 2], acc[0][i * 2 + 1]);
        }
        if (n >= 2 && n < 5) {
          put(0, n * 2 - 4);
          put(0, n * 2 - 3);
        }
        if (n == 6) publish(stb, lane);
      };
      stage(acc[3], 15, w_slot(15), 11, 1, [&](int j) {
        if (j == 1) keep_alive4(A, nv);
        row0(j);
      });
      stage(acc[3], 16, w_slot(16), 9, 1, [&](int j) { row0(6 + j); }, false);
      stage(acc[3], 17, w_slot(17), 13, 1, [](int) {}, false);
      if (!wg) mbar_wait(bars + (B_SR + 1) * 8);
      wgmma_wait<0>();
      acc_fence(acc[3]);
      stage_slab(acc[3], stg + w_stg(wg, 3), lane);
      publish(stb + 24, lane);
      mbar_wait(bars + B_RD * 8);
      if (lds32(bars + O_CNT) > NREC || imp >= 0x10000u) {
        ntiles = 4;
        tile0 = (x0 >> 3) + wg + (y0 << 5);
        tstep = 0x100;
      }
    } else if (strip) {
      const uint32_t tab = sbase + SM_GT + wid * 1152;
      {
        const int r = (warp & 1) * 4 + (lane & 3), c = lane >> 2, pu = wid * 4 + (lane & 3), pv = x0 + c;
        const uint32_t oa = sbase + SM_GO + (wid >> 1) * 2304 + (left ? c * 8 + r : r * 8 + c) * 36, swap = left ? 0x3210u : 0x1032u;
        uint32_t bad = 0;
        mbar_wait(bars + B_OG * 8);
#pragma unroll 1
        for (int tv = 0; tv < 3; tv++) {
          const uint32_t base = pack2((float)(pv + tv - 1), (float)pu);
#pragma unroll
          for (int tu = 0; tu < 3; tu++) {
            const int tap = left ? tv * 3 + tu : tu * 3 + tv;
            const uint32_t gp = hadd2(base, tap_delta(1, tu));
            uint32_t d = hsub2(clip2(hadd2(gp, prmt(lds32(oa + tap * 4), 0, swap))), clip2(gp));
            const bool out = tu == 0 && pu == 0, off = strip_off(d, out);
            bad |= off ? 1u << tap : 0u;
            d = out ? 0x3f800000u : off ? 0u : d & 0xffff0000u;
            sts32(tab + tv * 384 + tu * 128 + lane * 4, d | ((int)d < 0 ? 0x7654u : 0x3210u));
          }
        }
        if (bad && pv >= 34) push_taps(bars, strip_key(pu, pv, left), bad, offs);
        __syncwarp();
        arrive_if(lane == 0 ? bars + B_SG * 8 : 0u);
      }
      wgmma_fence();
      wgmma_def(acc[1], w_desc(SB), never);
      wgmma_def(acc[0], w_desc(SB), never);
      wgmma_commit();
      wgmma_wait<0>();
      uint32_t la[3];
#pragma unroll
      for (int tv = 0; tv < 3; tv++) {
        const int p = (warp * 4 + ((lane >> 3) & 1)) * 10 + min((lane & 7) + tv, IW - x0);
        la[tv] = sbase + wg * GWIN + p * 64 + ((((lane >> 4) ^ (p >> 1)) & 3) << 4);
      }
      uint32_t D[2][8][2], A[3][8], dl[3][4];
#pragma unroll
      for (int i = 0; i < 6; i++) ldsm4(A[0] + i * 4, tab);
#pragma unroll
      for (int tu = 0; tu < 3; tu++) lds128(dl[tu], tab + tu * 128 + (lane >> 2) * 16);
      auto fetch = [&](int b, uint32_t a) {
#pragma unroll
        for (int i = 0; i < 4; i++) ldsm4(D[b][2 * i][0], D[b][2 * i + 1][0], D[b][2 * i][1], D[b][2 * i + 1][1], (a ^ (((i + b) & 1) * 32)) + i * 2 * GROW);
      };
      mbar_wait(bars + (B_XF + wg * 3) * 8);
      fetch(0, la[0]);
      int tn = 1;
#pragma unroll 1
      for (int st = 0; st < 9; st++) {
        const uint64_t bd = w_desc(SB + SM_GW) + (st < 7 ? st : st - 7) * (STAGE >> 4);
        mbar_wait(bars + (B_WF + st) * 8);
#pragma unroll
        for (int kh = 0; kh < 2; kh++) {
          if (kh && tn == 0) mbar_wait(bars + (B_XF + wg * 3 + (st >= 5 ? 2 : 1)) * 8);
          fetch(kh ^ 1, la[kh]);
          uint32_t E[7][2];
#pragma unroll
          for (int tu = 0; tu < 3; tu++) {
            wgmma_wait<2>();
            keep_alive8(A[tu], nv);
            if (kh == 1 && tu == 0) arrive_if((st == 1 || st == 2) && lane < 2 ? we_addr + st * 8 - 8 : 0u);
#pragma unroll
            for (int i = 0; i < 8; i++) {
              const int r = (i >> 2) * 2 + (i & 1), h = (i >> 1) & 1;
              if (tu == 0 && r == 0) E[0][h] = hsub2(D[kh][1][h], D[kh][0][h]);
              if (tu == 0 || r == 3) E[r + tu + 1][h] = hsub2(D[kh][r + tu + 2][h], D[kh][r + tu + 1][h]);
              A[tu][i] = hfma2_h(dl[tu][r], 1, prmt(E[r + tu + 1][h], E[r + tu][h], dl[tu][r]), D[kh][r + tu + 1][h]);
              if ((i & 3) == 3) {
                wgmma_fence();
                wgmma_rs(acc[i >> 2], A[tu] + (i & 4), bd + tu * WTAP + kh * WHALF, kh + tu ? 1 : st);
              }
            }
            wgmma_commit();
            if (kh) lds128(dl[tu], tab + tn * 384 + tu * 128 + (lane >> 2) * 16);
          }
        }
        const uint32_t l0 = la[0] + (st < 6 ? GSLICE : 0);
        la[0] = la[1];
        la[1] = la[2];
        la[2] = l0;
        tn = tn == 2 ? 0 : tn + 1;
      }
      mbar_wait(bars + B_IM * 8);
      mbar_wait(bars + B_SG * 8);
      uint32_t n0, imp, sel[2];
      lds64(n0, imp, bars + O_CNT);
      lds64(sel[0], sel[1], bars + O_SEL + (lane & 3) * 8);
      wgmma_wait<0>();
#pragma unroll
      for (int i = 0; i < 3; i++) keep_alive8(A[i], nv);
      if (__any_sync(0xffffffffu, (imp >> (wg * 4)) & 1)) {
        const uint32_t code = (wg * 512 + warp * 32 + (lane >> 2) + 0x4000u) * 0x10001u;
        select_rows(A[0], sel, code, false);
        select_rows(A[0] + 4, sel, code + 0x100010u, false);
        wgmma_fence();
        wgmma_rs(acc[0], A[0], w_desc(SB + SM_FIX));
        wgmma_rs(acc[1], A[0] + 4, w_desc(SB + SM_FIX));
        wgmma_commit();
        wgmma_wait<0>();
        keep_alive8(A[0], nv);
      }
      if (__any_sync(0xffffffffu, n0 > NREC || imp >= 0x10000u)) {
        ntiles = 2;
        tile0 = left ? wg * 2 + (x0 << 5) : (x0 >> 3) + (wg << 9);
        tstep = left ? 1 : 0x100;
      }
      acc_fence(acc[0]);
      acc_fence(acc[1]);
      bar_sync(1 + wg, 128);
      const uint32_t stg = sbase + wg * GWIN + warp * 2048;
      stage_slab<8192>(acc[0], stg, lane);
      stage_slab<8192>(acc[1], stg + 1024, lane);
      publish(bars + (B_ST + wg * 4) * 8, lane);
    } else {
      ntiles = !wg || cta >= -4;
      tile0 = corner_tile(wg);
      if (!ntiles) {
        arrive_if(lane == 0 ? bars + B_SG * 8 : 0u);
        if (own) {
          const uint32_t key = src < 7 ? wino_key(oy, ox) : strip_key(along, 32 + (t & 1), !lf);
          const uint32_t base = pack2((float)oy, (float)ox), swap = lf ? 0x3210u : 0x1032u, lim = src < 7 ? 0u : 0x3f00u;
          const uint32_t lim0 = along ? lim : 0u, limy = lf ? lim0 : lim, limx = lf ? lim : lim0;
          uint32_t bad = 0;
#pragma unroll
          for (int m = 0; m < 9; m++) {
            const uint32_t gp = hadd2(base, tap_delta(m / 3, m % 3));
            o2[m] = clip2(hadd2(gp, o2[m]));
            bad |= (prmt(hsub2(o2[m], clip2(gp)), 0, swap) & 0x7fff7fffu) > (m == 0 ? lim0 : m < 3 ? limy : m % 3 == 0 ? limx : lim) ? 1u << m : 0u;
          }
#pragma unroll 1
          for (; bad; bad &= bad - 1) {
            const int m = __ffs(bad) - 1;
            uint32_t pos = o2[0];
#pragma unroll
            for (int i = 1; i < 9; i++) pos = m == i ? o2[i] : pos;
            push_record(bars, key | (m << 16), pos);
          }
        }
        bar_sync(2, 128);
        const int n = __shfl_sync(0xffffffffu, lds32(bars + O_CNT), 0);
        if (n && n <= NREC) {
          const int r0 = warp ? 99 : lane >> 2;
          const uint32_t k0 = lds32(bars + O_REC + (lane >> 2) * 8), k1 = lds32(bars + O_REC + 64 + (lane >> 2) * 8);
          const uint32_t t0 = r0 < n ? (k0 >> 16) & 15 : 15, t1 = r0 + 8 < n ? (k1 >> 16) & 15 : 15;
          const uint32_t taps = __reduce_or_sync(0xffffffffu, lane < n ? 1u << ((lds32(bars + O_REC + (lane & 15) * 8) >> 16) & 15) : 0u);
          wgmma_fence();
          wgmma_def(acc[0], w_desc(SB), never);
          wgmma_commit();
          wgmma_wait<0>();
          const uint32_t tmp = sbase + SM_CX + CWIN;
#pragma unroll 1
          for (int i = t; i < n * 12; i += 128) {
            const int r = (i * 171) >> 11;
            uint32_t key, pos, v[4];
            lds64(key, pos, bars + O_REC + r * 8);
            delta(v, key, pos, reinterpret_cast<const uint4*>(x), i - r * 12);
            sts128(tmp + (r + i) * 16, v);
          }
          if (warp == 3) {
#pragma unroll 1
            for (int st = 0; st < 9; st++) mbar_wait(bars + (B_WF + st) * 8);
          }
          bar_sync(2, 128);
          uint32_t D[6][4];
#pragma unroll
          for (int k = 0; k < 6; k++) ldsm4(D[k], tmp + (lane & 15) * 208 + (lane >> 4) * 16 + k * 32);
#pragma unroll 1
          for (uint32_t m = taps; m; m &= m - 1) {
            const uint32_t tap = __ffs(m) - 1, ki = (tap * 11) >> 5;
            uint32_t A[6][4];
#pragma unroll
            for (int k = 0; k < 6; k++) {
#pragma unroll
              for (int i = 0; i < 4; i++) A[k][i] = (i & 1 ? t1 : t0) == tap ? D[k][i] : 0u;
            }
            wgmma_fence();
#pragma unroll
            for (int k = 0; k < 6; k++)
              wgmma_rs(acc[0], A[k], w_desc(SB) + ((k >> 1) * 3 + ki) * (STAGE >> 4) + (tap - ki * 3) * WTAP + (k & 1) * WHALF, k ? 1 : m ^ taps);
            wgmma_commit();
            wgmma_wait<0>();
#pragma unroll
            for (int k = 0; k < 3; k++) keep_alive8(A[2 * k], nv);
          }
          acc_fence(acc[0]);
          if (!warp) {
            uint32_t* dst = reinterpret_cast<uint32_t*>(scr->fix) + src * 768 + (lane >> 2) * 16 + (lane & 3);
#pragma unroll
            for (int j = 0; j < 24; j++) dst[(j >> 3) * 256 + (j & 1) * 128 + ((((j >> 1) ^ (lane >> 3)) & 3) << 2)] = pack2(acc[0][j * 2], acc[0][j * 2 + 1]);
          }
        }
        if (!warp) {
          __threadfence();
          __syncwarp();
          if (lane < NREC)
            asm volatile("st.relaxed.gpu.global.v2.u32 [%0], {%1, %2};\n" ::"l"(scr->key + src * NREC + lane), "r"(lds32(bars + O_REC + lane * 8)),
                         "r"((tag << 8) | min(n, 99)) : "memory");
          if (lane == 0) scr->launch[blockIdx.x] = tag;
        }
      }
    }
    if (ntiles) {
      const uint32_t winb = sbase + SM_CX + wg * CWIN, tab = sbase + SM_CT + wid * 1152;
      const uint32_t ck = (uint32_t)(lane >> 4) << 4, again = tstep != 0;
      if (tstep) {
        mbar_wait(bars + B_FX * 8);
        bar_sync(3, 256);
        if (wid == 0 && one) {
#pragma unroll 1
          for (int st = 0; st < 9; st++) load_cw(st);
        }
        __syncwarp();
      }
#pragma unroll 1
      for (int n = 0; n < ntiles; n++) {
        const uint32_t tl = tile0 + n * tstep;
        const int wx0 = (int)(tl & 255) * 8 - 2, wy0 = (int)(tl >> 8) * 8 - 2;
        if (tstep && warp == 0 && one) {
#pragma unroll 1
          for (int g = 0; g < 3; g++) load_cx(wg, g, tl);
        }
        __syncwarp();
        uint32_t mout = 0, need = 0, of[5];
        {
          const int ph = wy0 + 2 + 2 * warp + ((lane >> 3) & 1), pw = wx0 + 2 + (lane & 7);
          if (tstep) {
#pragma unroll
            for (int k = 0; k < 5; k++) of[k] = __ldg(offs + (ph * IW + pw) * 9 + min((lane >> 4) + 2 * k, 8));
          } else {
            mbar_wait(bars + B_OG * 8);
#pragma unroll
            for (int k = 0; k < 5; k++) of[k] = lds32(winb + 2 * CSLICE + (warp * 16 + (lane & 15)) * 36 + min((lane >> 4) + 2 * k, 8) * 4);
          }
#pragma unroll 1
          for (int m = lane >> 4; m < 9; m += 2) {
            const int ki = (m * 11) >> 5;
            const uint32_t pos = clip2(hadd2(pack2((float)(ph + ki - 1), (float)(pw + m - ki * 3 - 1)), of[0]));
#pragma unroll
            for (int k = 0; k < 4; k++) of[k] = of[k + 1];
            const uint32_t iy = (int)bf16lo(pos) - wy0, ix = (int)bf16hi(pos) - wx0, f = frac2(pos);
            mout |= max(iy, ix) > 10 ? 1u << m : 0u;
            need |= ((f >> 16 ? 1u : 0u) | (f & 0xffffu ? 0x200u : 0u) | (f >> 16 && f & 0xffffu ? 0x40000u : 0u)) << m;
            const uint32_t pp = (iy * 12 + ix) * 0x10001u + 0x10000u;
            sts32(tab + m * 64 + (lane & 7) * 8 + ((lane >> 1) & 4), f);
            sts32(tab + 576 + m * 64 + (lane & 15) * 4, pp * 64 + ((pp << 3) & 0x300030u));
            of[4] = pos;
          }
          mout = __reduce_or_sync(0xffffffffu, mout);
          need = __reduce_or_sync(0xffffffffu, need);
          arrive_if(lane == 0 && !tstep ? bars + B_SG * 8 : 0u);
        }
        uint32_t outside;
        asm volatile("{\n.reg .pred p, q;\nsetp.ne.u32 p, %1, 0;\nbarrier.red.or.pred q, %2, 128, p;\nselp.u32 %0, 1, 0, q;\n}\n"
                     : "=r"(outside) : "r"(mout), "r"(1 + wg) : "memory");
        outside = __shfl_sync(0xffffffffu, outside, 0);
        wgmma_fence();
        wgmma_def(acc[0], w_desc(SB), never);
        wgmma_commit();
        wgmma_wait<0>();
        if (!outside) {
          uint32_t T[3][4], C[2][3][4];
#pragma unroll
          for (int i = 0; i < 9; i++) ldsm4(i < 3 ? T[i] : C[0][i - 3], tab);
          uint32_t ad[4];
          auto fetch = [&](int k, uint32_t e, uint32_t slice, uint32_t nd) {
            if (!(k & 1)) {
              ad[0] = (e & 0xffffu) + slice;
              ad[1] = (e >> 16) + slice;
              ad[2] = ad[0] ^ 32;
              ad[3] = ad[1] ^ 32;
            }
            ldsm4_if(T[k % 3], ad[(k & 1) * 2], never ^ 1);
            ldsm4_if(C[k & 1][0], ad[(k & 1) * 2 + 1], nd & 1);
            ldsm4_if(C[k & 1][1], ad[2 - (k & 1) * 2] + CROW, nd & 0x200u);
            ldsm4_if(C[k & 1][2], ad[3 - (k & 1) * 2] + CROW, nd & 0x40000u);
          };
          uint32_t ent[3], slice = winb;
          const uint32_t ck2 = ck * 0x10001u;
          mbar_wait(bars + (B_XF + wg * 3) * 8, (n + again) & 1);
          fetch(0, lds32(tab + 576 + (lane & 15) * 4) ^ ck2, slice, need);
          int ki = 0, g = 0;
#pragma unroll 1
          for (int st = 0; st < 9; st++) {
            const uint64_t bd = w_desc(SB) + st * (STAGE >> 4);
            const int kn = ki == 2 ? 0 : ki + 1;
            uint32_t cf[3][4];
#pragma unroll
            for (int j = 0; j < 3; j++) {
              uint32_t wA, wB;
              lds64(wA, wB, tab + (ki * 3 + j) * 64 + (lane >> 2) * 8);
              ent[j] = lds32(tab + 576 + (j < 2 ? ki * 3 + j + 1 : kn * 3) * 64 + (lane & 15) * 4) ^ ck2;
              coefs(wA, cf[j][0], cf[j][1]);
              coefs(wB, cf[j][2], cf[j][3]);
            }
            if (kn == 0 && g < 2) mbar_wait(bars + (B_XF + wg * 3 + g + 1) * 8, (n + again) & 1);
            mbar_wait(bars + (B_WF + st) * 8, again);
#pragma unroll
            for (int k = 0; k < 6; k++) {
              wgmma_wait<1>();
              if (k == 5 && kn == 0 && g < 2) {
                g++;
                slice += CSLICE;
              }
              fetch(k + 1, ent[k >> 1], slice, need >> (k < 5 ? ki * 3 + ((k + 1) >> 1) : kn * 3));
              blend4(T[k % 3], C[k & 1][0], C[k & 1][1], C[k & 1][2], cf[k >> 1][0], cf[k >> 1][1], cf[k >> 1][2], cf[k >> 1][3]);
              wgmma_fence();
              wgmma_rs(acc[0], T[k % 3], bd + (k >> 1) * WTAP + (k & 1) * WHALF, k ? 1 : st);
              wgmma_commit();
            }
            ki = kn;
          }
          wgmma_wait<0>();
          keep_alive8(T[0], nv);
          keep_alive8(T[1], nv);
        } else {
#pragma unroll
          for (int k = 0; k < 5; k++) {
            const int m = 2 * k - (lane >> 4);
            if (m >= 0) sts32(tab + m * 64 + (lane & 7) * 8 + ((lane >> 1) & 4), of[k]);
          }
          __syncwarp();
          uint32_t buf[2][8];
#pragma unroll
          for (int i = 0; i < 16; i++) buf[0][i] = nv;
          const uint32_t tmp = tab + 576 + lane * 16;
          int tap = 0, g = 0;
#pragma unroll 1
          for (int d = 0;; d += 2) {
#pragma unroll
            for (int b = 0; b < 2; b++) {
              const int k = d + b, q = (k * 11) >> 5;
              if (k == 27) goto tile_done;
              mbar_wait(bars + (B_XF + wg * 3 + g) * 8, (n + again) & 1);
              mbar_wait(bars + (B_WF + q) * 8, again);
              const uint32_t pos = lds32(tab + tap * 64 + (lane & 7) * 8 + ((lane >> 1) & 4));
              const int gy = (int)bf16lo(pos), gx = (int)bf16hi(pos);
              uint32_t T[8];
              if (!((mout >> tap) & 1)) {
                uint32_t wA, wB, pA0, pA1, pB0, pB1, G[4], H[4], K[4];
                lds64(wA, wB, tab + tap * 64 + (lane >> 2) * 8);
                const uint32_t slice = winb + g * CSLICE;
                const uint32_t p = (gy - wy0) * 12 + gx - wx0, p1 = p + 1;
                const uint32_t a00 = slice + p * 64 + (((p << 3) & 0x30) ^ ck), a01 = slice + p1 * 64 + (((p1 << 3) & 0x30) ^ ck);
                coefs(frac2(wA), pA0, pA1);
                coefs(frac2(wB), pB0, pB1);
#pragma unroll
                for (int hf = 0; hf < 2; hf++) {
                  ldsm4(T + hf * 4, a00 ^ (hf * 32));
                  ldsm4(G, a01 ^ (hf * 32));
                  ldsm4(H, (a00 + CROW) ^ (hf * 32) ^ 32);
                  ldsm4(K, (a01 + CROW) ^ (hf * 32) ^ 32);
                  blend4(T + hf * 4, G, H, K, pA0, pA1, pB0, pB1);
                }
              } else {
                uint32_t q0, q1;
                coefs(frac2(pos), q0, q1);
                const int sx = gx < IW - 1 ? IC / 8 : 0, sy = gy < IH - 1 ? IW * IC / 8 : 0;
                const uint4* pc = reinterpret_cast<const uint4*>(x) + (gy * IW + gx) * (IC / 8) + g * 4 + (lane >> 4);
#pragma unroll
                for (int hf = 0; hf < 2; hf++) {
                  uint4 v[4];
                  v[0] = __ldg(pc + hf * 2);
                  v[1] = __ldg(pc + hf * 2 + sx);
                  v[2] = __ldg(pc + hf * 2 + sy);
                  v[3] = __ldg(pc + hf * 2 + sy + sx);
                  blend4(&v[0].x, &v[1].x, &v[2].x, &v[3].x, q0, q1, q0, q1);
                  __syncwarp();
                  sts128(tmp, &v[0].x);
                  __syncwarp();
                  ldsm4(T + hf * 4, tmp);
                }
              }
              wgmma_wait<1>();
              keep_alive8(buf[b], nv);
#pragma unroll
              for (int i = 0; i < 8; i++) asm volatile("xor.b32 %0, %1, %2;\n" : "=r"(buf[b][i]) : "r"(T[i]), "r"(nv));
              const uint64_t bd = w_desc(SB) + q * (STAGE >> 4) + (k - q * 3) * WTAP;
              wgmma_fence();
              wgmma_rs(acc[0], buf[b], bd, k);
              wgmma_rs(acc[0], buf[b] + 4, bd + WHALF);
              wgmma_commit();
              if (++tap == 9) {
                tap = 0;
                g++;
              }
            }
          }
        tile_done:
          wgmma_wait<0>();
          keep_alive8(buf[0], nv);
          keep_alive8(buf[1], nv);
        }
        acc_fence(acc[0]);
        bar_sync(1 + wg, 128);
        stage_slab(acc[0], winb + warp * 1024, lane);
        fence_async();
        bar_sync(1 + wg, 128);
        if (warp == 0 && one) {
          tma_store(&tm.out[3], winb, wx0 + 2, wy0 + 2, 0);
          asm volatile("cp.async.bulk.wait_group.read 0;\n" ::: "memory");
        }
      }
    }
  } else if (wid < 12) {
    asm volatile("setmaxnreg.dec.sync.aligned.u32 40;\n");
    if (prep) {
      const int lane = lane_now();
      uint32_t u[4][4];
      weights4<true>(&g[0].x, &g[1].x, &g[2].x, u);
      const uint8_t* udst = scr->u + ((cta >> 2) & 1) * (4 * STAGE) + (cta & 2) * (STAGE / 4) + ((cta - NW) >> 3) * 3072 + (wid - 8) * 1024 +
                            (cta & 1) * 512 + (lane >> 2) * 64 + (((lane ^ (lane >> 3)) & 3) << 4);
#pragma unroll
      for (int k = 0; k < 4; k++)
        asm volatile("st.relaxed.gpu.global.v4.b32 [%0], {%1, %2, %3, %4};\n" ::"l"(udst + k * STAGE), "r"(u[k][0]), "r"(u[k][1]), "r"(u[k][2]), "r"(u[k][3]) : "memory");
      uint32_t chk = 0;
#pragma unroll
      for (int k = 0; k < 4; k++) {
        uint32_t v;
        asm volatile("ld.relaxed.gpu.global.b32 %0, [%1];\n" : "=r"(v) : "l"(udst + k * STAGE) : "memory");
        chk |= v;
      }
      chk = __reduce_or_sync(0xffffffffu, chk & never);
      if (one) asm volatile("red.relaxed.gpu.global.add.u32 [%0], %1;\n" ::"l"(scr->cnt), "r"(chk + 1) : "memory");
    }
    asm volatile("barrier.cluster.wait.acquire.aligned;\n" ::: "memory");
    const int w = wid - 8, lane = lane_now();
    uint32_t asked = 1;
    if (wino) {
      bar_sync(12, 384);
      arrive_if(one ? bars + (B_WF + w) * 8 : 0u);
      const int hi = w >> 1, ty = (w & 1) * 4 + (lane >> 4) * 2;
      const bool bottom = y0 + 4 * ty + 8 == IH;
      uint32_t d0[4][2], dm[2][2][2], d1[4][2];
      auto fetch0 = [&](int e, uint32_t src, bool low) {
#pragma unroll
        for (int r = 0; r < 4; r++) lds64(d0[r][0], d0[r][1], src + r * 128);
        lds64(dm[e][0][0], dm[e][0][1], src + 4 * 128);
        lds64(dm[e][1][0], dm[e][1][1], src + (low && bottom ? 4 * 128 : 5 * 128));
      };
      uint32_t src = sbase + SM_R + hi * PIECE + ty * 512 + (lane & 15) * 8;
      uint32_t v0 = sbase + ty * VROW + hi * 128 + (lane & 8) * 8 + (lane & 1) * 8 + ((((lane >> 1) ^ (ty + hi)) & 3) << 4);
      const uint32_t x1 = hi ? 48 : 16;
      mbar_wait(bars + (B_XF + 2) * 8);
      fetch0(0, src + 4 * VSLOT - SM_R + (4 - hi) * PIECE + hi * 512, hi);
      transform6<2>(d0, d0 + 2, dm[0], v0 + 512 + hi * (VROW - 128), 10 * VSLOT);
      publish(bars + B_V0 * 8, !one);
      mbar_wait(bars + B_V0 * 8);
      mbar_wait(bars + (B_VF + 1) * 8);
      v0 += 4 * VSLOT;
      mbar_wait(bars + (B_XF + 5) * 8);
      fetch0(0, src, false);
#pragma unroll 1
      for (int nn = 0; nn < 4; nn++) {
        const int s = nn >> 1, jj = (nn & 1) * 2;
        const uint32_t xf = bars + (B_XF + 6 + s * 5 + jj) * 8, off0 = s ? 12 * VSLOT : 4 * VSLOT;
        asm volatile("" : "+r"(src), "+r"(v0));
        if (nn == 2) mbar_wait(bars + B_VE * 8);
#pragma unroll
        for (int e = 0; e < 2; e++) {
          const int j = jj + e;
          const uint32_t next = xf + (e ? (nn == 1 ? 16 : 8) : 0);
          const uint32_t ready = mbar_poll(next);
#pragma unroll
          for (int r = 0; r < 3; r++) lds64(d1[r][0], d1[r][1], src + e * 2 * PIECE + (6 + r) * 128);
          lds64(d1[3][0], d1[3][1], src + e * 2 * PIECE + (bottom ? 8 * 128 : 9 * 128));
          transform6<2>(d0, d0 + 2, dm[e], (v0 ^ e * 32) + e * 256, off0);
          if (!ready) mbar_wait(next);
          if (e) src += jj ? -4 * PIECE : 4 * PIECE;
          if (!e || nn < 3) fetch0(e ^ 1, src + (e ^ 1) * 2 * PIECE, false);
          transform6<2>(dm[e], d1, d1 + 2, (v0 ^ x1 ^ e * 32) + e * 256 + VROW, off0);
          __syncwarp();
          arrive_if(one && (!s || j == 2) ? bars + (B_RE + j + s * 3) * 8 : 0u);
          if (j + hi == 2 || j == 3) publish(bars + (j == 3 ? B_VB + 1 + s : B_VF + 2 + s * 2) * 8, !one);
        }
        v0 += jj ? -4 * VSLOT - 512 : 512;
      }
      mbar_wait(bars + B_OF * 8);
      uint32_t mx = 0;
#pragma unroll
      for (int h = 0; h < 2; h++) {
        uint32_t v[6][4];
#pragma unroll
        for (int k = 0; k < 6 - 3 * h; k++) lds128(v[k], sbase + SM_R + w * 4608 + (h * 6 + k) * 512 + lane * 16);
#pragma unroll
        for (int k = 0; k < 6 - 3 * h; k++) mx = absmax2(mx, absmax2(absmax2(v[k][0], v[k][1]), absmax2(v[k][2], v[k][3])));
      }
      const uint32_t lim = (pack2((float)max(y0 + w * 8, 34) - 1.5f, (float)max(x0, 34) - 1.5f) & 0x7f807f80u) - 0x04000400u;
      uint32_t who = __ballot_sync(0xffffffffu, (mx & 0x7fffu) >= (lim & 0xffffu) || (mx & 0x7fff0000u) >= (lim & 0xffff0000u));
      asm volatile("{\n.reg .pred p, q;\nsetp.ne.u32 p, %1, 0;\nbarrier.red.or.pred q, 4, 128, p;\nselp.u32 %0, 1, 0, q;\n}\n"
                   : "=r"(asked) : "r"(who) : "memory");
      arrive_if(!asked && w == 0 && one ? bars + B_RD * 8 : 0u);
#pragma unroll 1
      for (; who; who &= who - 1) {
#pragma unroll 1
        for (int k = lane; k < 64; k += 32) {
          const int wd = (k >> 2) * 128 + (__ffs(who) - 1) * 4 + (k & 3), c = (wd * 7282) >> 16, tap = wd - c * 9, ki = (tap * 11) >> 5;
          const int y = y0 + w * 8 + (c >> 4), xx = x0 + (c & 15);
          if (k < 36 && min(y, xx) >= 34) {
            const uint32_t gp = pack2((float)(y + ki - 1), (float)(xx + tap - ki * 3 - 1));
            const uint32_t pos = clip2(hadd2(gp, lds32(sbase + SM_R + w * 4608 + wd * 4)));
            if (pos != clip2(gp)) push_record(bars, wino_key(y, xx) | (tap << 16), pos);
          }
          __syncwarp();
        }
      }
      bar_sync(4, 128);
    }
    if (wino || strip) {
      if (strip) mbar_wait(bars + B_SG * 8);
      const uint32_t n0 = __shfl_sync(0xffffffffu, lds32(bars + O_CNT), 0);
      arrive_if(w == 0 && one && asked ? bars + B_RD * 8 : 0u);
      if (n0 <= NREC) fixup(bars, w, n0, reinterpret_cast<const uint4*>(x), wgt);
      if (w == 0) {
        arrive_if(one ? bars + B_FX * 8 : 0u);
        mbar_wait(bars + B_IM * 8);
        if (one) atomicAdd(scr->launch + blockIdx.x, 1);
      }
    }
  } else {
    asm volatile("setmaxnreg.dec.sync.aligned.u32 24;\n");
    asm volatile("barrier.cluster.wait.acquire.aligned;\n" ::: "memory");
    auto wait_all = [&](uint32_t dt) {
      while (__shfl_sync(0xffffffffu, clock32(), 0) - tstart < dt) __nanosleep(40);
    };
    if (wid == 15 && !wino) {
      const uint32_t dst = sbase + (strip ? SM_GW : 0) + (cta & 1) * (STAGE / 2);
      int g = 0, r = 0;
#pragma unroll 1
      for (int k = 0; k < 9; k++) {
        if (strip && k >= 7) mbar_wait(bars + (B_WE + k - 7) * 8);
        else wait_all(strip ? GW0 + k * GWS : CW0 + k * CWS);
        if (one) {
          mbar_expect_tx(bars + (B_WF + k) * 8, STAGE);
          tma_load_w(dst + (strip && k >= 7 ? k - 7 : k) * STAGE, &tm.w[left], bars + (B_WF + k) * 8, g + (cta & 1) * 16, left ? 0 : r, left ? r : 0, 3);
        }
        if (++r == 3) {
          r = 0;
          g += 32;
        }
      }
    }
    if (wid >= 13 && wid < 15 && !wino) {
      const int r = 14 - wid;
      const uint32_t tl = corner_tile(r);
#pragma unroll 1
      for (int g = 0; g < 3; g++) {
        if (g == 2) mbar_wait(bars + B_SG * 8);
        wait_all(strip ? (r ? GX1 + g * GXS1 : GX0 + g * GXS + (g >> 1) * GXE) : CX0 + g * CXS);
        if (one && (strip || (g && (!r || cta >= -4))))
          tma_load_x(sbase + (strip ? r * GWIN + g * GSLICE : SM_CX + r * CWIN + g * CSLICE), &tm.x[strip ? 1 + left : 3],
                     bars + (B_XF + r * 3 + g) * 8, strip ? GSLICE : CSLICE, g * 32, strip ? x0 - 1 : (int)(tl & 255) * 8 - 2,
                     strip ? r * 16 - 2 : (int)(tl >> 8) * 8 - 2);
      }
    }
    if (wid == 15) {
      if (wino) {
        wait_all(PDELAY);
        asm volatile(
            "{\n.reg .pred p;\n.reg .u32 n, v;\nmov.u32 n, 0;\n"
            "W_%=:\n"
            "ld.relaxed.gpu.global.u32 v, [%0];\nsetp.ge.u32 p, v, 72;\nvote.sync.all.pred p, p, 0xffffffff;\n"
            "@p bra D_%=;\n"
            "add.u32 n, n, 1;\nsetp.lt.u32 p, n, 0x100000;\n@p bra W_%=;\ntrap;\n"
            "D_%=:\nfence.proxy.async.global;\n}\n" ::"l"(scr->cnt)
            : "memory");
#pragma unroll 1
        for (int k = 0; k < 8; k++) {
          mbar_wait(bars + (B_WE + ((0x77654210u >> (4 * k)) & 15)) * 8);
          if (one)
            bulk_load_mc(sbase + (uint32_t)((w_slots(4, 1, 8) >> (8 * k)) & 255) * 1024 + (cta & 1) * (STAGE / 2),
                         scr->u + (k * 2 + (cta & 1)) * (STAGE / 2), STAGE / 2, bars + (B_WF + 4 + k) * 8);
        }
        if (one) atomicInc(scr->cnt, 72 + NW - 1);
#pragma unroll
        for (int k = 0; k < 6; k++) {
          if (k > 0 && k < 5) mbar_wait(bars + (B_WE + min(7 + k, 11)) * 8);
          if (one)
            tma_load_w(sbase + (uint32_t)((w_slots(12, 1, 6) >> (8 * k)) & 255) * 1024 + (cta & 1) * (STAGE / 2), &tm.w[1],
                       bars + (B_WF + 12 + k) * 8, (k < 3 ? k : k - 3) * 32 + (cta & 1) * 16, 0, k < 3 ? 0 : 2, 3);
        }
      }
    } else if (wid == 14) {
      if (wino) {
#pragma unroll 1
        for (int s = 1; s < 3; s++) {
#pragma unroll
          for (int j = 0; j < 5; j++) {
            if (s == 2) mbar_wait(bars + (B_RE + j) * 8);
            else if (j == 0 || j == 2) wait_all(j ? SDELAY + SDELAY2 : SDELAY);
            if (one) load_cols(s, j);
          }
        }
      }
    } else if (wino || strip) {
      const int wg = wid - 12;
      if (one) {
        if (wino && wg) {
#pragma unroll 1
          for (int i = 4; i < 18; i++) mbar_expect_tx(bars + (B_WF + i) * 8, STAGE);
        } else if (wino) {
#pragma unroll 1
          for (int i = 0; i < 15; i++) mbar_expect_tx(bars + (B_XF + i) * 8, (0x4210 >> i) & 1 ? PIECE : 2 * PIECE);
        }
        asm volatile("prefetch.tensormap [%0];\n" ::"l"(reinterpret_cast<uint64_t>(&tm.out[wino ? 0 : 1 + left])) : "memory");
      }
      if (wino && !wg) {
        if (one) {
          wait_until(tstart, FDELAY);
          asm volatile("cp.async.bulk.prefetch.tensor.2d.L2.global [%0, {%1, %2}];\n" ::"l"(reinterpret_cast<uint64_t>(&tm.o[0])), "r"(x0 * 9), "r"(y0) : "memory");
          mbar_expect_tx(bars + B_OF * 8, 2 * VSLOT);
          mbar_wait(bars + B_R2 * 8);
          tma_load_o(sbase + SM_R, &tm.o[0], bars + B_OF * 8, x0, y0);
        }
        bar_sync(7, 32);
      }
      if (wg == wino) {
        bar_sync(6, 32);
        const int lane = lane_now();
        const uint32_t tag = scr->launch[blockIdx.x] + 1;
        uint32_t n = 0;
        if (x0 == 32 || (wino && y0 == 32)) {
          wait_all(IDELAY);
          const int src = !wino ? 7 : ry ? (ry + 7) >> 1 : (0xfea550u >> (2 * cta)) & 3;
          uint32_t key, v;
          asm volatile(
              "{\n.reg .pred p;\n.reg .u32 n, t;\nmov.u32 n, 0;\n"
              "W_%=:\n"
              "ld.acquire.gpu.global.v2.u32 {%0, %1}, [%2];\nxor.b32 t, %1, %3;\nsetp.lt.u32 p, t, 256;\nvote.sync.all.pred p, p, 0xffffffff;\n"
              "@p bra D_%=;\n"
              "nanosleep.u32 40;\nadd.u32 n, n, 1;\nsetp.lt.u32 p, n, 0x100000;\n@p bra W_%=;\ntrap;\n"
              "D_%=:\nfence.proxy.async.global;\n}\n"
              : "=r"(key), "=r"(v)
              : "l"(scr->key + src * NREC + (lane & 15)), "r"(tag << 8)
              : "memory");
          v &= 255;
          const uint32_t dy = (key & 255) - (wino ? y0 : left ? 32 : 0), dx = ((key >> 8) & 255) - (wino || !left ? x0 : 0);
          const bool mine = lane < v && dy < 32 && dx < (left ? 32 : 16);
          n = __reduce_or_sync(0xffffffffu, v > NREC ? 0x10000u : mine ? 1u << (key >> 27) : 0u);
          put_sel(bars, mine ? key : ~0u, lane);
          if (n && n < 256 && one) {
            asm volatile("mbarrier.expect_tx.relaxed.cta.shared::cta.b64 [%0], 3072;\n" ::"r"(bars + B_IM * 8) : "memory");
            asm volatile("cp.async.bulk.shared::cluster.global.mbarrier::complete_tx::bytes [%0], [%1], 3072, [%2];\n" ::"r"(sbase + SM_FIX),
                         "l"(scr->fix + src * 192), "r"(bars + B_IM * 8) : "memory");
          }
          __syncwarp();
        }
        if (lane == 0) sts32(bars + O_CNT + 4, n + (tag & never));
        __syncwarp();
        arrive_if(lane == 0 ? bars + B_IM * 8 : 0u);
      }
      mbar_wait(bars + B_IM * 8);
      mbar_wait(bars + B_RD * 8);
      uint32_t n0, imp;
      lds64(n0, imp, bars + O_CNT);
      if (__all_sync(0xffffffffu, n0 <= NREC && imp < 0x10000u)) {
        const int lane = lane_now();
        const uint32_t key = lane < n0 ? lds32(bars + O_REC + lane * 8) : ~0u;
        const CUtensorMap* map = &tm.out[wino ? 0 : 1 + left];
        const int c1 = x0 + (wino ? wg * 8 : 0), c3 = wino ? y0 >> 2 : 0;
#pragma unroll 1
        for (int i = wino ? 2 : 0;; i = (i - 1) & 3) {
          const uint32_t stg = sbase + (wino ? w_stg(wg, i) : wg * GWIN), sb = bars + (B_ST + wg * 4 + i) * 8;
          uint32_t mask = __ballot_sync(0xffffffffu, key >> 27 == wg * 4 + i);
          if (mask) {
            mbar_wait(bars + B_FX * 8);
#pragma unroll 1
            do {
              const uint32_t r = __ffs(mask) - 1, m = (__shfl_sync(0xffffffffu, key, r) >> 20) & 127, l = min(lane, 23);
              const uint32_t a = stg + (l >> 3) * (wino ? 4096 : 8192) + m * 64 + ((((l ^ m) >> 1) & 3) << 4) + (l & 1) * 8;
              uint32_t v[2], c[2];
              lds64(c[0], c[1], sbase + SM_FIX + 3072 + r * 192 + l * 8);
              mbar_wait(sb);
              lds64(v[0], v[1], a);
              v[0] = hadd2(v[0], c[0]);
              v[1] = hadd2(v[1], c[1]);
              sts64(a, v);
              mask &= mask - 1;
            } while (mask);
            fence_async();
            __syncwarp();
          }
          mbar_wait(sb);
          if (one) tma_store(map, stg, c1, wino ? i : wg * 16, c3);
          if (!wg && wino && i < 2) {
            asm volatile("cp.async.bulk.wait_group.read 1;\n" ::: "memory");
            arrive_if(one ? bars + (B_SR + 1 - i) * 8 : 0u);
          }
          if (i == 3 || !wino) break;
        }
        asm volatile("cp.async.bulk.wait_group.read 0;\n" ::: "memory");
      } else {
        arrive_if(one ? bars + (B_SR + wg) * 8 : 0u);
      }
    }
  }
}

typedef CUresult (*EncodeTiledFn)(CUtensorMap*, CUtensorMapDataType, cuuint32_t, void*, const cuuint64_t*,
                                  const cuuint64_t*, const cuuint32_t*, const cuuint32_t*, CUtensorMapInterleave,
                                  CUtensorMapSwizzle, CUtensorMapL2promotion, CUtensorMapFloatOOBfill);

}

extern "C" void kernel_launch(void* const* d_in, const int* in_sizes, int n_in, void* d_out, int out_size) {
  static EncodeTiledFn encode = nullptr;
  static void* scratch = nullptr;
  if (!encode) {
    cudaGetSymbolAddress(&scratch, g_scratch);
    void* fn = nullptr;
    cudaDriverEntryPointQueryResult qres;
    cudaGetDriverEntryPoint("cuTensorMapEncodeTiled", &fn, cudaEnableDefault, &qres);
    encode = (EncodeTiledFn)fn;
    cudaFuncSetAttribute(dcn_kernel, cudaFuncAttributeMaxDynamicSharedMemorySize, SMEM_BYTES);
  }
  Maps tm;
  const cuuint32_t es[5] = {1, 1, 1, 1, 1};
  constexpr cuuint64_t PX = IC * 2, ROW = IW * IC * 2;
  for (int i = 0; i < 4; i++) {
    const cuuint64_t dims[3] = {IC, IW, IH};
    const cuuint64_t strides[2] = {i == 2 ? ROW : PX, i == 2 ? PX : ROW};
    const cuuint32_t box[4][3] = {{32, 2, 34}, {32, 10, 20}, {32, 10, 20}, {32, 12, 12}};
    encode(&tm.x[i], CU_TENSOR_MAP_DATA_TYPE_BFLOAT16, 3, d_in[0], dims, strides, box[i], es, CU_TENSOR_MAP_INTERLEAVE_NONE,
           i ? CU_TENSOR_MAP_SWIZZLE_64B : CU_TENSOR_MAP_SWIZZLE_NONE, CU_TENSOR_MAP_L2_PROMOTION_NONE,
           CU_TENSOR_MAP_FLOAT_OOB_FILL_NONE);
  }
  {
    const cuuint64_t dims[4] = {IC, 2, IH, IW / 2 - 1};
    const cuuint64_t strides[3] = {PX, ROW, 2 * PX};
    const cuuint32_t box[4] = {32, 2, 34, 2};
    encode(&tm.x[4], CU_TENSOR_MAP_DATA_TYPE_BFLOAT16, 4, (char*)d_in[0] + PX, dims, strides, box, es, CU_TENSOR_MAP_INTERLEAVE_NONE,
           CU_TENSOR_MAP_SWIZZLE_NONE, CU_TENSOR_MAP_L2_PROMOTION_NONE, CU_TENSOR_MAP_FLOAT_OOB_FILL_NONE);
  }
  for (int i = 0; i < 2; i++) {
    const cuuint64_t dims[5] = {32, IC, 3, 3, 3};
    const cuuint64_t strides[4] = {IC * 2, 64, IC * IC * 2, 3 * IC * IC * 2};
    const cuuint32_t box[5] = {32, 16, 3, i ? 3u : 1u, i ? 1u : 3u};
    encode(&tm.w[i], CU_TENSOR_MAP_DATA_TYPE_BFLOAT16, 5, d_in[2], dims, strides, box, es, CU_TENSOR_MAP_INTERLEAVE_NONE,
           CU_TENSOR_MAP_SWIZZLE_64B, CU_TENSOR_MAP_L2_PROMOTION_L2_128B, CU_TENSOR_MAP_FLOAT_OOB_FILL_NONE);
  }
  for (int i = 0; i < 2; i++) {
    const cuuint64_t dims[2] = {IW * 9, IH};
    const cuuint64_t strides[1] = {IW * 36};
    const cuuint32_t box[2] = {i ? 72u : 144u, i ? 8u : 32u};
    encode(&tm.o[i], CU_TENSOR_MAP_DATA_TYPE_UINT32, 2, d_in[1], dims, strides, box, es, CU_TENSOR_MAP_INTERLEAVE_NONE,
           CU_TENSOR_MAP_SWIZZLE_NONE, CU_TENSOR_MAP_L2_PROMOTION_NONE, CU_TENSOR_MAP_FLOAT_OOB_FILL_NONE);
  }
  for (int i = 0; i < 4; i++) {
    const cuuint64_t dims[5] = {32, IW, i ? IH : 4u, i ? 1u : IH / 4, 3};
    const cuuint64_t strides[4] = {i == 2 ? ROW : PX, i == 2 ? PX : ROW, 4 * ROW, 64};
    const cuuint32_t box[5] = {32, 8, i == 3 ? 8u : i ? 16u : 1u, i ? 1u : 8u, 3};
    encode(&tm.out[i], CU_TENSOR_MAP_DATA_TYPE_BFLOAT16, 5, d_out, dims, strides, box, es, CU_TENSOR_MAP_INTERLEAVE_NONE,
           CU_TENSOR_MAP_SWIZZLE_64B, CU_TENSOR_MAP_L2_PROMOTION_NONE, CU_TENSOR_MAP_FLOAT_OOB_FILL_NONE);
  }
  dcn_kernel<<<GRID, NTHREADS, SMEM_BYTES>>>((const __nv_bfloat16*)d_in[0], (const uint32_t*)d_in[1], (const uint4*)d_in[2],
                                             (Scratch*)scratch, 0u, tm);
}
```
